```python
import torch

def _softmax(x, axis=-1):
    return torch.softmax(x, dim=axis)
def _gelu(x):
    return torch.nn.functional.gelu(x, approximate="tanh")
def _silu(x):
    return torch.nn.functional.silu(x)
def _sigmoid(x):
    return torch.sigmoid(x)
def _layernorm(x, axis=-1, eps=1e-5):
    m = x.mean(dim=axis, keepdim=True)
    v = x.var(dim=axis, keepdim=True, unbiased=False)
    return (x - m) / torch.sqrt(v + eps)
def _scatter_add(tgt, idx, src, axis=0):
    return tgt.clone().index_add_(axis, idx, src)
def _segment_sum(src, seg, n):
    out = torch.zeros((n,) + src.shape[1:], dtype=src.dtype)
    return out.index_add_(0, seg, src)
def _pad(x, pw):
    flat = tuple(v for pair in reversed(pw) for v in pair)
    return torch.nn.functional.pad(x, flat)

kernel_name = 'gather_scatter__hybrid_graph_tf_graphgps__graph'

def setup_inputs():

    _w = (lambda a: (lambda t: t.to(torch.bfloat16) if t.is_floating_point() else t)(torch.as_tensor(a)))
    N, deg, D = 10000, 16, 256
    E = N * deg
    src = (lambda lo, hi, *s: torch.randint(lo, hi, s))(0, N, E).to(torch.int64)
    dst = (lambda lo, hi, *s: torch.randint(lo, hi, s))(0, N, E).to(torch.int64)
    deg_cnt = torch.bincount(dst, minlength=N).to(float) + 1.0
    sc = 1.0 / float(D) ** 0.5
    return {
        "x": _w((lambda *s: torch.randn(*s, dtype=torch.bfloat16) * 0.05)(N, D)),
        "src": _w(src),
        "dst": _w(dst),
        "deg_inv": _w((1.0 / deg_cnt).to(float)),
        "w_msg": _w((lambda *s: torch.randn(*s, dtype=torch.bfloat16) * 0.2)(D, D) * sc),
        "wq": _w((lambda *s: torch.randn(*s, dtype=torch.bfloat16) * 1.6)(D, D) * sc),
        "wk": _w((lambda *s: torch.randn(*s, dtype=torch.bfloat16) * 1.6)(D, D) * sc),
        "wv": _w((lambda *s: torch.randn(*s, dtype=torch.bfloat16) * 0.2)(D, D) * sc),
        "w_out": _w((lambda *s: torch.randn(*s, dtype=torch.bfloat16) * 0.2)(D, D) * sc),
    }

def reference(x, src, dst, deg_inv, w_msg, wq, wk, wv, w_out):
    N, D = x.shape[0], x.shape[1]
    h = _layernorm(x, axis=-1)
    m_e = torch.einsum('nd,de->ne', h, w_msg)
    h_local = _segment_sum(m_e[src], dst, N) * deg_inv[:, None]
    q = torch.einsum('nd,de->ne', h, wq)
    k = torch.einsum('nd,de->ne', h, wk)
    v = torch.einsum('nd,de->ne', h, wv)
    logits = torch.einsum('id,jd->ij', q, k) / (float(D) ** 0.5)
    attn = _softmax(logits, axis=-1)
    h_global = torch.einsum('ij,jd->id', attn, v)
    y = torch.einsum('nd,de->ne', h_local + h_global, w_out)
    return x + y
```

```cpp
#include <cuda_runtime.h>
#include <cuda_bf16.h>
#include <stdint.h>

namespace {

constexpr int N_ = 10000, E_ = 160000, NQT = 79, NPAD = NQT * 128;
constexpr int BN = 80, NKV = 125, NST = 3, STB = BN * 512, NCTA = 132;
constexpr int NSLOT = NQT + 26;
#define SCHED_A 75
#define SCHED_B 77
#define SCHED_C 77
#define SCHED_B1 23
#define XDEPTH 3
#define XEARLY 0
constexpr int SM_Q = 0, SM_RING = 65536, SM_REM = SM_RING + NST * STB, SM_AUX = SM_REM + 8192, SM_META = SM_AUX + 32768;
constexpr int SM_BAR = SM_META + 1024, SM_TOTAL = SM_BAR + 1536;
constexpr unsigned CNT_W = 96 * 4, CNT_H = NCTA, CNT_M = NCTA, CNT_G = NCTA * 2;

struct Scratch {
  unsigned ctr[5 * 32], epoch, pad0[31], pflag[NSLOT * 2], pad1[1024 - 6 * 32 - NSLOT * 2];
  uint8_t w[3 * 131072];
  float2 meta[NSLOT * 128];
  uint8_t ht[NPAD * 512];
  uint8_t qt[NPAD * 512];
  uint8_t mp[NPAD * 512];
  uint8_t acc[NCTA * 40960];
  uint8_t part[NSLOT * 65536];
};
__device__ __align__(1024) Scratch g_scratch;
#define STAMP(i)
#define PROF_DUMP()

constexpr uint32_t DESC_HI = 0x40000100u;
__device__ __forceinline__ void wgmma_qk(float (&d)[40], uint32_t da, uint32_t db, int sd) {
  asm volatile("{\n.reg .pred p;\n.reg .b64 da, db;\nmov.b64 da, {%40, %43};\nmov.b64 db, {%41, %43};\nsetp.ne.b32 p, %42, 0;\n"
    "wgmma.mma_async.sync.aligned.m64n80k16.f32.bf16.bf16 {%0, %1, %2, %3, %4, %5, %6, %7, %8, %9, %10, %11, %12, %13, %14, %15, %16, %17, %18, %19, %20, %21, %22, %23, %24, %25, %26, %27, %28, %29, %30, %31, %32, %33, %34, %35, %36, %37, %38, %39}, da, db, p, 1, 1, 0, 0;\n}\n"
    : "+f"(d[0]), "+f"(d[1]), "+f"(d[2]), "+f"(d[3]), "+f"(d[4]), "+f"(d[5]), "+f"(d[6]), "+f"(d[7]), "+f"(d[8]), "+f"(d[9]), "+f"(d[10]), "+f"(d[11]), "+f"(d[12]), "+f"(d[13]), "+f"(d[14]), "+f"(d[15]), "+f"(d[16]), "+f"(d[17]), "+f"(d[18]), "+f"(d[19]), "+f"(d[20]), "+f"(d[21]), "+f"(d[22]), "+f"(d[23]), "+f"(d[24]), "+f"(d[25]), "+f"(d[26]), "+f"(d[27]), "+f"(d[28]), "+f"(d[29]), "+f"(d[30]), "+f"(d[31]), "+f"(d[32]), "+f"(d[33]), "+f"(d[34]), "+f"(d[35]), "+f"(d[36]), "+f"(d[37]), "+f"(d[38]), "+f"(d[39])
    : "r"(da), "r"(db), "r"(sd), "r"(DESC_HI));
}

__device__ __forceinline__ void wgmma_rs256(float (&d)[128], uint32_t a0, uint32_t a1, uint32_t a2, uint32_t a3, uint32_t db, int sd) {
  asm volatile("{\n.reg .pred p;\n.reg .b64 da, db;\nmov.b64 db, {%132, %134};\nsetp.ne.b32 p, %133, 0;\n"
    "wgmma.mma_async.sync.aligned.m64n256k16.f32.bf16.bf16 {%0, %1, %2, %3, %4, %5, %6, %7, %8, %9, %10, %11, %12, %13, %14, %15, %16, %17, %18, %19, %20, %21, %22, %23, %24, %25, %26, %27, %28, %29, %30, %31, %32, %33, %34, %35, %36, %37, %38, %39, %40, %41, %42, %43, %44, %45, %46, %47, %48, %49, %50, %51, %52, %53, %54, %55, %56, %57, %58, %59, %60, %61, %62, %63, %64, %65, %66, %67, %68, %69, %70, %71, %72, %73, %74, %75, %76, %77, %78, %79, %80, %81, %82, %83, %84, %85, %86, %87, %88, %89, %90, %91, %92, %93, %94, %95, %96, %97, %98, %99, %100, %101, %102, %103, %104, %105, %106, %107, %108, %109, %110, %111, %112, %113, %114, %115, %116, %117, %118, %119, %120, %121, %122, %123, %124, %125, %126, %127}, {%128, %129, %130, %131}, db, p, 1, 1, 1;\n}\n"
    : "+f"(d[0]), "+f"(d[1]), "+f"(d[2]), "+f"(d[3]), "+f"(d[4]), "+f"(d[5]), "+f"(d[6]), "+f"(d[7]), "+f"(d[8]), "+f"(d[9]), "+f"(d[10]), "+f"(d[11]), "+f"(d[12]), "+f"(d[13]), "+f"(d[14]), "+f"(d[15]), "+f"(d[16]), "+f"(d[17]), "+f"(d[18]), "+f"(d[19]), "+f"(d[20]), "+f"(d[21]), "+f"(d[22]), "+f"(d[23]), "+f"(d[24]), "+f"(d[25]), "+f"(d[26]), "+f"(d[27]), "+f"(d[28]), "+f"(d[29]), "+f"(d[30]), "+f"(d[31]), "+f"(d[32]), "+f"(d[33]), "+f"(d[34]), "+f"(d[35]), "+f"(d[36]), "+f"(d[37]), "+f"(d[38]), "+f"(d[39]), "+f"(d[40]), "+f"(d[41]), "+f"(d[42]), "+f"(d[43]), "+f"(d[44]), "+f"(d[45]), "+f"(d[46]), "+f"(d[47]), "+f"(d[48]), "+f"(d[49]), "+f"(d[50]), "+f"(d[51]), "+f"(d[52]), "+f"(d[53]), "+f"(d[54]), "+f"(d[55]), "+f"(d[56]), "+f"(d[57]), "+f"(d[58]), "+f"(d[59]), "+f"(d[60]), "+f"(d[61]), "+f"(d[62]), "+f"(d[63]), "+f"(d[64]), "+f"(d[65]), "+f"(d[66]), "+f"(d[67]), "+f"(d[68]), "+f"(d[69]), "+f"(d[70]), "+f"(d[71]), "+f"(d[72]), "+f"(d[73]), "+f"(d[74]), "+f"(d[75]), "+f"(d[76]), "+f"(d[77]), "+f"(d[78]), "+f"(d[79]), "+f"(d[80]), "+f"(d[81]), "+f"(d[82]), "+f"(d[83]), "+f"(d[84]), "+f"(d[85]), "+f"(d[86]), "+f"(d[87]), "+f"(d[88]), "+f"(d[89]), "+f"(d[90]), "+f"(d[91]), "+f"(d[92]), "+f"(d[93]), "+f"(d[94]), "+f"(d[95]), "+f"(d[96]), "+f"(d[97]), "+f"(d[98]), "+f"(d[99]), "+f"(d[100]), "+f"(d[101]), "+f"(d[102]), "+f"(d[103]), "+f"(d[104]), "+f"(d[105]), "+f"(d[106]), "+f"(d[107]), "+f"(d[108]), "+f"(d[109]), "+f"(d[110]), "+f"(d[111]), "+f"(d[112]), "+f"(d[113]), "+f"(d[114]), "+f"(d[115]), "+f"(d[116]), "+f"(d[117]), "+f"(d[118]), "+f"(d[119]), "+f"(d[120]), "+f"(d[121]), "+f"(d[122]), "+f"(d[123]), "+f"(d[124]), "+f"(d[125]), "+f"(d[126]), "+f"(d[127])
    : "r"(a0), "r"(a1), "r"(a2), "r"(a3), "r"(db), "r"(sd), "r"(DESC_HI));
}

__device__ __forceinline__ void wgmma_ss256(float (&d)[128], uint32_t da, uint32_t db, int sd) {
  asm volatile("{\n.reg .pred p;\n.reg .b64 da, db;\nmov.b64 da, {%128, %131};\nmov.b64 db, {%129, %131};\nsetp.ne.b32 p, %130, 0;\n"
    "wgmma.mma_async.sync.aligned.m64n256k16.f32.bf16.bf16 {%0, %1, %2, %3, %4, %5, %6, %7, %8, %9, %10, %11, %12, %13, %14, %15, %16, %17, %18, %19, %20, %21, %22, %23, %24, %25, %26, %27, %28, %29, %30, %31, %32, %33, %34, %35, %36, %37, %38, %39, %40, %41, %42, %43, %44, %45, %46, %47, %48, %49, %50, %51, %52, %53, %54, %55, %56, %57, %58, %59, %60, %61, %62, %63, %64, %65, %66, %67, %68, %69, %70, %71, %72, %73, %74, %75, %76, %77, %78, %79, %80, %81, %82, %83, %84, %85, %86, %87, %88, %89, %90, %91, %92, %93, %94, %95, %96, %97, %98, %99, %100, %101, %102, %103, %104, %105, %106, %107, %108, %109, %110, %111, %112, %113, %114, %115, %116, %117, %118, %119, %120, %121, %122, %123, %124, %125, %126, %127}, da, db, p, 1, 1, 0, 1;\n}\n"
    : "+f"(d[0]), "+f"(d[1]), "+f"(d[2]), "+f"(d[3]), "+f"(d[4]), "+f"(d[5]), "+f"(d[6]), "+f"(d[7]), "+f"(d[8]), "+f"(d[9]), "+f"(d[10]), "+f"(d[11]), "+f"(d[12]), "+f"(d[13]), "+f"(d[14]), "+f"(d[15]), "+f"(d[16]), "+f"(d[17]), "+f"(d[18]), "+f"(d[19]), "+f"(d[20]), "+f"(d[21]), "+f"(d[22]), "+f"(d[23]), "+f"(d[24]), "+f"(d[25]), "+f"(d[26]), "+f"(d[27]), "+f"(d[28]), "+f"(d[29]), "+f"(d[30]), "+f"(d[31]), "+f"(d[32]), "+f"(d[33]), "+f"(d[34]), "+f"(d[35]), "+f"(d[36]), "+f"(d[37]), "+f"(d[38]), "+f"(d[39]), "+f"(d[40]), "+f"(d[41]), "+f"(d[42]), "+f"(d[43]), "+f"(d[44]), "+f"(d[45]), "+f"(d[46]), "+f"(d[47]), "+f"(d[48]), "+f"(d[49]), "+f"(d[50]), "+f"(d[51]), "+f"(d[52]), "+f"(d[53]), "+f"(d[54]), "+f"(d[55]), "+f"(d[56]), "+f"(d[57]), "+f"(d[58]), "+f"(d[59]), "+f"(d[60]), "+f"(d[61]), "+f"(d[62]), "+f"(d[63]), "+f"(d[64]), "+f"(d[65]), "+f"(d[66]), "+f"(d[67]), "+f"(d[68]), "+f"(d[69]), "+f"(d[70]), "+f"(d[71]), "+f"(d[72]), "+f"(d[73]), "+f"(d[74]), "+f"(d[75]), "+f"(d[76]), "+f"(d[77]), "+f"(d[78]), "+f"(d[79]), "+f"(d[80]), "+f"(d[81]), "+f"(d[82]), "+f"(d[83]), "+f"(d[84]), "+f"(d[85]), "+f"(d[86]), "+f"(d[87]), "+f"(d[88]), "+f"(d[89]), "+f"(d[90]), "+f"(d[91]), "+f"(d[92]), "+f"(d[93]), "+f"(d[94]), "+f"(d[95]), "+f"(d[96]), "+f"(d[97]), "+f"(d[98]), "+f"(d[99]), "+f"(d[100]), "+f"(d[101]), "+f"(d[102]), "+f"(d[103]), "+f"(d[104]), "+f"(d[105]), "+f"(d[106]), "+f"(d[107]), "+f"(d[108]), "+f"(d[109]), "+f"(d[110]), "+f"(d[111]), "+f"(d[112]), "+f"(d[113]), "+f"(d[114]), "+f"(d[115]), "+f"(d[116]), "+f"(d[117]), "+f"(d[118]), "+f"(d[119]), "+f"(d[120]), "+f"(d[121]), "+f"(d[122]), "+f"(d[123]), "+f"(d[124]), "+f"(d[125]), "+f"(d[126]), "+f"(d[127])
    : "r"(da), "r"(db), "r"(sd), "r"(DESC_HI));
}

__device__ __forceinline__ void wgmma_rs72(float (&d)[36], uint32_t a0, uint32_t a1, uint32_t a2, uint32_t a3, uint32_t db, int sd) {
  asm volatile("{\n.reg .pred p;\n.reg .b64 da, db;\nmov.b64 db, {%40, %42};\nsetp.ne.b32 p, %41, 0;\n"
    "wgmma.mma_async.sync.aligned.m64n72k16.f32.bf16.bf16 {%0, %1, %2, %3, %4, %5, %6, %7, %8, %9, %10, %11, %12, %13, %14, %15, %16, %17, %18, %19, %20, %21, %22, %23, %24, %25, %26, %27, %28, %29, %30, %31, %32, %33, %34, %35}, {%36, %37, %38, %39}, db, p, 1, 1, 0;\n}\n"
    : "+f"(d[0]), "+f"(d[1]), "+f"(d[2]), "+f"(d[3]), "+f"(d[4]), "+f"(d[5]), "+f"(d[6]), "+f"(d[7]), "+f"(d[8]), "+f"(d[9]), "+f"(d[10]), "+f"(d[11]), "+f"(d[12]), "+f"(d[13]), "+f"(d[14]), "+f"(d[15]), "+f"(d[16]), "+f"(d[17]), "+f"(d[18]), "+f"(d[19]), "+f"(d[20]), "+f"(d[21]), "+f"(d[22]), "+f"(d[23]), "+f"(d[24]), "+f"(d[25]), "+f"(d[26]), "+f"(d[27]), "+f"(d[28]), "+f"(d[29]), "+f"(d[30]), "+f"(d[31]), "+f"(d[32]), "+f"(d[33]), "+f"(d[34]), "+f"(d[35])
    : "r"(a0), "r"(a1), "r"(a2), "r"(a3), "r"(db), "r"(sd), "r"(DESC_HI));
}

__device__ __forceinline__ void wgmma_rs64t(float (&d)[36], uint32_t a0, uint32_t a1, uint32_t a2, uint32_t a3, uint32_t db, int sd) {
  asm volatile("{\n.reg .pred p;\n.reg .b64 da, db;\nmov.b64 db, {%36, %38};\nsetp.ne.b32 p, %37, 0;\n"
    "wgmma.mma_async.sync.aligned.m64n64k16.f32.bf16.bf16 {%0, %1, %2, %3, %4, %5, %6, %7, %8, %9, %10, %11, %12, %13, %14, %15, %16, %17, %18, %19, %20, %21, %22, %23, %24, %25, %26, %27, %28, %29, %30, %31}, {%32, %33, %34, %35}, db, p, 1, 1, 1;\n}\n"
    : "+f"(d[0]), "+f"(d[1]), "+f"(d[2]), "+f"(d[3]), "+f"(d[4]), "+f"(d[5]), "+f"(d[6]), "+f"(d[7]), "+f"(d[8]), "+f"(d[9]), "+f"(d[10]), "+f"(d[11]), "+f"(d[12]), "+f"(d[13]), "+f"(d[14]), "+f"(d[15]), "+f"(d[16]), "+f"(d[17]), "+f"(d[18]), "+f"(d[19]), "+f"(d[20]), "+f"(d[21]), "+f"(d[22]), "+f"(d[23]), "+f"(d[24]), "+f"(d[25]), "+f"(d[26]), "+f"(d[27]), "+f"(d[28]), "+f"(d[29]), "+f"(d[30]), "+f"(d[31])
    : "r"(a0), "r"(a1), "r"(a2), "r"(a3), "r"(db), "r"(sd), "r"(0x40000040u));
}

__device__ __forceinline__ uint32_t mkdesc(uint32_t addr, uint32_t lbo) { return ((addr & 0x3FFFF) >> 4) | ((lbo >> 4) << 16); }
#define WG_FENCE() asm volatile("wgmma.fence.sync.aligned;\n" ::: "memory")
#define WG_COMMIT() asm volatile("wgmma.commit_group.sync.aligned;\n" ::: "memory")
#define WG_WAIT(n) asm volatile("wgmma.wait_group.sync.aligned %0;\n" ::"n"(n) : "memory")
template <int N> __device__ __forceinline__ void pin(float (&d)[N]) {
#pragma unroll
  for (int i = 0; i < N; i++) asm volatile("" : "+f"(d[i])::"memory");
}
#define PROXY_FENCE() asm volatile("fence.proxy.async;\n" ::: "memory")
#define PROXY_FENCE_SMEM() asm volatile("fence.proxy.async.shared::cta;\n" ::: "memory")

__device__ __forceinline__ void mbar_init(uint32_t bar, uint32_t cnt) { asm volatile("mbarrier.init.shared::cta.b64 [%0], %1;\n" ::"r"(bar), "r"(cnt) : "memory"); }
__device__ __forceinline__ void mbar_expect_tx(uint32_t bar, uint32_t bytes) { asm volatile("mbarrier.arrive.expect_tx.shared::cta.b64 _, [%0], %1;\n" ::"r"(bar), "r"(bytes) : "memory"); }
__device__ __forceinline__ void mbar_arrive(uint32_t bar) { asm volatile("mbarrier.arrive.shared::cta.b64 _, [%0];\n" ::"r"(bar) : "memory"); }
__device__ __forceinline__ void mbar_wait(uint32_t bar, uint32_t parity) {
  asm volatile("{\n.reg .pred p;\n.reg .u32 n;\n.reg .u64 z;\nmov.u64 z, 0;\nmov.u32 n, 0;\n"
               "LAB_WAIT:\n"
               "mbarrier.try_wait.parity.shared::cta.b64 p, [%0], %1;\n"
               "@p bra LAB_DONE;\n"
               "add.u32 n, n, 1;\n"
               "setp.gt.u32 p, n, 100000000;\n"
               "@p st.global.u32 [z], n;\n"
               "bra LAB_WAIT;\n"
               "LAB_DONE:\n}\n" ::"r"(bar), "r"(parity) : "memory");
}
__device__ __forceinline__ bool mbar_test(uint32_t bar, uint32_t parity) {
  uint32_t ok;
  asm volatile("{\n.reg .pred p;\nmbarrier.test_wait.parity.shared::cta.b64 p, [%1], %2;\nselp.u32 %0, 1, 0, p;\n}\n" : "=r"(ok) : "r"(bar), "r"(parity) : "memory");
  return __all_sync(~0u, ok);
}
__device__ __forceinline__ void gwait(const unsigned* p, unsigned target) {
  asm volatile("{\n.reg .pred p;\n.reg .u32 n, v;\n.reg .u64 z;\nmov.u64 z, 0;\nmov.u32 n, 0;\n"
               "LAB_WAIT:\n"
               "ld.relaxed.gpu.global.u32 v, [%0];\n"
               "sub.u32 v, v, %1;\n"
               "setp.ge.s32 p, v, 0;\n"
               "@p bra LAB_DONE;\n"
               "add.u32 n, n, 1;\n"
               "setp.gt.u32 p, n, 20000000;\n"
               "@p st.global.u32 [z], n;\n"
               "bra LAB_WAIT;\n"
               "LAB_DONE:\n}\n" ::"l"(p), "r"(target) : "memory");
}
#define GPU_FENCE() asm volatile("fence.acq_rel.gpu;\n" ::: "memory")
__device__ __forceinline__ void garrive(unsigned* p) { asm volatile("red.release.gpu.global.add.u32 [%0], 1;\n" ::"l"(p) : "memory"); }
__device__ __forceinline__ void garrive_bulk(unsigned* p) { asm volatile("red.relaxed.gpu.global.add.u32 [%0], 1;\n" ::"l"(p) : "memory"); }
__device__ __forceinline__ void gset(unsigned* p, unsigned v) { asm volatile("st.relaxed.gpu.global.u32 [%0], %1;\n" ::"l"(p), "r"(v) : "memory"); }
__device__ __forceinline__ void bulk_g2s(uint32_t dst, const void* src, uint32_t bytes, uint32_t bar) {
  asm volatile("cp.async.bulk.shared::cluster.global.mbarrier::complete_tx::bytes [%0], [%1], %2, [%3];\n" ::"r"(dst), "l"(src), "r"(bytes), "r"(bar) : "memory");
}
__device__ __forceinline__ void bar_sync(int id, int n) { asm volatile("bar.sync %0, %1;\n" ::"r"(id), "r"(n) : "memory"); }
__device__ __forceinline__ void bar_arrive(int id, int n) { asm volatile("bar.arrive %0, %1;\n" ::"r"(id), "r"(n) : "memory"); }
__device__ __forceinline__ float ex2(float x) { float y; asm("ex2.approx.ftz.f32 %0, %1;" : "=f"(y) : "f"(x)); return y; }
__device__ __forceinline__ float rcp(float x) { float y; asm volatile("rcp.approx.ftz.f32 %0, %1;" : "=f"(y) : "f"(x)); return y; }
__device__ __forceinline__ uint32_t pack2(float lo, float hi) { uint32_t r; asm("cvt.rn.bf16x2.f32 %0, %1, %2;" : "=r"(r) : "f"(hi), "f"(lo)); return r; }
__device__ __forceinline__ float blo(uint32_t v) { return __uint_as_float(v << 16); }
__device__ __forceinline__ float bhi(uint32_t v) { return __uint_as_float(v & 0xffff0000u); }
__device__ __forceinline__ uint4 ldg_nc(const void* p) { uint4 v; asm volatile("ld.global.nc.v4.u32 {%0,%1,%2,%3}, [%4];" : "=r"(v.x), "=r"(v.y), "=r"(v.z), "=r"(v.w) : "l"(p)); return v; }
__device__ __forceinline__ uint4 ldg_cg(const void* p) { uint4 v; asm volatile("ld.global.cg.v4.u32 {%0,%1,%2,%3}, [%4];" : "=r"(v.x), "=r"(v.y), "=r"(v.z), "=r"(v.w) : "l"(p) : "memory"); return v; }
__device__ __forceinline__ void stg128(void* p, uint32_t a, uint32_t b, uint32_t c, uint32_t d) { asm volatile("st.global.v4.u32 [%0], {%1,%2,%3,%4};" ::"l"(p), "r"(a), "r"(b), "r"(c), "r"(d) : "memory"); }
__device__ __forceinline__ void sts128(uint32_t p, uint32_t a, uint32_t b, uint32_t c, uint32_t d) { asm volatile("st.shared.v4.u32 [%0], {%1,%2,%3,%4};" ::"r"(p), "r"(a), "r"(b), "r"(c), "r"(d) : "memory"); }
__device__ __forceinline__ uint4 lds128(uint32_t p) { uint4 v; asm volatile("ld.shared.v4.u32 {%0,%1,%2,%3}, [%4];" : "=r"(v.x), "=r"(v.y), "=r"(v.z), "=r"(v.w) : "r"(p) : "memory"); return v; }
__device__ __forceinline__ float quad_sum(float v) { v += __shfl_xor_sync(~0u, v, 1); return v + __shfl_xor_sync(~0u, v, 2); }
__device__ __forceinline__ float quad_max(float v) { v = fmaxf(v, __shfl_xor_sync(~0u, v, 1)); return fmaxf(v, __shfl_xor_sync(~0u, v, 2)); }
__device__ __forceinline__ void mma16816(float (&d)[4], uint32_t a0, uint32_t a1, uint32_t a2, uint32_t a3, uint32_t b0, uint32_t b1) {
  asm("mma.sync.aligned.m16n8k16.row.col.f32.bf16.bf16.f32 {%0,%1,%2,%3}, {%4,%5,%6,%7}, {%8,%9}, {%0,%1,%2,%3};"
               : "+f"(d[0]), "+f"(d[1]), "+f"(d[2]), "+f"(d[3]) : "r"(a0), "r"(a1), "r"(a2), "r"(a3), "r"(b0), "r"(b1));
}
__device__ __forceinline__ uint32_t comp(const uint4& v, int i) { return i == 0 ? v.x : i == 1 ? v.y : i == 2 ? v.z : v.w; }
__device__ __forceinline__ void bulk_s2g(void* dst, uint32_t src, uint32_t bytes) {
  asm volatile("cp.async.bulk.global.shared::cta.bulk_group [%0], [%1], %2;\n" ::"l"(dst), "r"(src), "r"(bytes) : "memory");
}
#define BULK_COMMIT() asm volatile("cp.async.bulk.commit_group;\n" ::: "memory")
#define BULK_WAIT_READ() asm volatile("cp.async.bulk.wait_group.read 0;\n" ::: "memory")
#define BULK_WAIT() asm volatile("cp.async.bulk.wait_group 0;\n" ::: "memory")
__device__ __forceinline__ void cp16(uint32_t dst, const void* src) { asm volatile("cp.async.cg.shared.global [%0], [%1], 16;\n" ::"r"(dst), "l"(src) : "memory"); }
__device__ __forceinline__ void ldsm4(uint32_t (&r)[4], uint32_t p) {
  asm volatile("ldmatrix.sync.aligned.m8n8.x4.shared.b16 {%0,%1,%2,%3}, [%4];" : "=r"(r[0]), "=r"(r[1]), "=r"(r[2]), "=r"(r[3]) : "r"(p));
}
__device__ __forceinline__ void stsm4(uint32_t p, uint32_t a, uint32_t b, uint32_t c, uint32_t d) {
  asm volatile("stmatrix.sync.aligned.m8n8.x4.shared.b16 [%0], {%1,%2,%3,%4};" ::"r"(p), "r"(a), "r"(b), "r"(c), "r"(d) : "memory");
}
__device__ __forceinline__ uint32_t hfma2(uint32_t a, uint32_t b, uint32_t c) { uint32_t r; asm("fma.rn.bf16x2 %0, %1, %2, %3;" : "=r"(r) : "r"(a), "r"(b), "r"(c)); return r; }
__device__ __forceinline__ uint32_t hadd2(uint32_t a, uint32_t b) { uint32_t r; asm("add.rn.bf16x2 %0, %1, %2;" : "=r"(r) : "r"(a), "r"(b)); return r; }

__device__ __forceinline__ void product_load(const bool qk, const __nv_bfloat16* __restrict__ L, const __nv_bfloat16* __restrict__ R,
                                             int d0, int c0, uint32_t sm) {
  const int tid = threadIdx.x, ch = tid & 31, w = tid >> 5;
  const uint32_t smr = sm + 40 * 512;
#pragma unroll
  for (int i = 0; i < 4; i++) {
    const int r = w + i * 12;
    if (r < 40) cp16(sm + r * 512 + ((ch ^ (r & 7)) << 4), L + (r < 32 ? d0 + r : 216 + r) * 256 + ch * 8);
  }
#pragma unroll
  for (int i = 0; i < 6; i++) {
    const int r = w + i * 12, e = r * 4 + (ch >> 3);
    if (qk) cp16(smr + (r >> 3) * 4096 + (ch >> 3) * 1024 + (r & 7) * 128 + (((ch ^ r) & 7) << 4), R + (r < 64 ? c0 + r : 184 + r) * 256 + ch * 8);
    else if (r < 64) cp16(smr + e * 128 + (((ch ^ e) & 7) << 4), R + e * 256 + c0 + (ch & 7) * 8);
  }
}
__device__ __forceinline__ void product_mma(const bool qk, uint8_t* img, int d0, int c0, uint32_t sm, unsigned* ctr) {
  const int lane = threadIdx.x & 31, w = (threadIdx.x >> 5) & 3, l7 = lane & 7;
  const uint32_t pa = sm + (((lane & 8) ? 32 : w * 8) + l7) * 512;
  uint32_t a[16][4];
#pragma unroll
  for (int u = 0; u < 16; u++) ldsm4(a[u], pa + (u >> 2) * 128 + ((((u & 3) * 2 + (lane >> 4)) ^ l7) << 4));
  float m[36];
#pragma unroll
  for (int i = 0; i < 36; i++) m[i] = 0.f;
  const uint32_t bd = mkdesc(sm + 40 * 512, 16);
  if (qk) {
    WG_FENCE();
#pragma unroll
    for (int u = 0; u < 16; u++) wgmma_rs72(m, a[u][0], a[u][1], a[u][2], a[u][3], bd + (u >> 2) * 64 + (u & 3) * 2, 1);
    WG_COMMIT();
    WG_WAIT(0);
    pin(m);
  } else {
    WG_FENCE();
#pragma unroll
    for (int u = 0; u < 16; u++) wgmma_rs64t(m, a[u][0], a[u][1], a[u][2], a[u][3], bd + u * 128, 1);
    WG_COMMIT();
    WG_WAIT(0);
    pin(m);
  }
  if (threadIdx.x == 256) STAMP(27);
  float z = quad_sum(m[34] + m[35]);
#pragma unroll
  for (int o = 4; o < 32; o *= 2) {
#pragma unroll
    for (int n = 0; n < 8; n++) { m[4 * n + 2] += __shfl_xor_sync(~0u, m[4 * n + 2], o); m[4 * n + 3] += __shfl_xor_sync(~0u, m[4 * n + 3], o); }
    z += __shfl_xor_sync(~0u, z, o);
  }
  const int g = lane >> 2, t = lane & 3, d = d0 + w * 8;
  const float u = quad_sum(m[32] + m[33]) - z * 0.125f;
  const float sc = d + g == 255 ? 0.f : qk ? 1.4426950408889634f / 16.f : 1.f;
  uint32_t v[8];
#pragma unroll
  for (int n = 0; n < 8; n++) v[n] = pack2(fmaf(m[4 * n + 2] + u, -0.125f, m[4 * n]) * sc, fmaf(m[4 * n + 3] + u, -0.125f, m[4 * n + 1]) * sc);
  const uint32_t so = sm + 57344 + w * 1024;
  if (qk) {
    if (c0 == 192 && t == 3) v[7] &= 0xffffu;
    const uint32_t p = so + l7 * 128 + (((lane >> 3) ^ l7) << 4);
    stsm4(p, v[0], v[1], v[2], v[3]); stsm4(p ^ 64, v[4], v[5], v[6], v[7]);
  } else {
    const uint32_t p = so + g * 128 + ((t ^ g) << 4);
    sts128(p, v[0], v[1], v[2], v[3]); sts128(p ^ 64, v[4], v[5], v[6], v[7]);
  }
  PROXY_FENCE_SMEM();
  __syncwarp();
  if (lane == 0) {
    if (threadIdx.x == 256) STAMP(31);
    bulk_s2g(img + (d >> 3) * 4096 + (c0 >> 6) * 1024, so, 1024);
    BULK_COMMIT();
    BULK_WAIT();
    garrive_bulk(ctr);
  }
  __syncwarp();
}

__global__ void __launch_bounds__(384, 1)
gps_kernel(const __nv_bfloat16* __restrict__ x, const int* __restrict__ src, const int* __restrict__ dst,
           const __nv_bfloat16* __restrict__ deg_inv, const __nv_bfloat16* __restrict__ w_msg,
           const __nv_bfloat16* __restrict__ wq, const __nv_bfloat16* __restrict__ wk, const __nv_bfloat16* __restrict__ wv,
           const __nv_bfloat16* __restrict__ w_out, __nv_bfloat16* __restrict__ out, Scratch* G) {
  extern __shared__ __align__(1024) uint8_t smem_raw[];
  const uint32_t sb = (uint32_t)__cvta_generic_to_shared(smem_raw);
  const uint32_t ring = sb + SM_RING, full0 = sb + SM_BAR, empty0 = full0 + 8 * NST, qbar0 = empty0 + 8 * NST;
  const uint32_t evt0 = qbar0 + 16, hread = evt0 + 112, auxfree = hread + 8, zready = auxfree + 8, sbar0 = zready + 8;
  const uint32_t wsent = sbar0 + 16, cbar = wsent + 8, xbar0 = cbar + 8;
  const int wg = __shfl_sync(~0u, threadIdx.x >> 7, 0);
  const int lane = threadIdx.x & 31;
  const int cta = blockIdx.x;
  if (threadIdx.x == 0) STAMP(0);

  const int grp = cta / 5, role = cta < 130 ? cta - grp * 5 : (cta == 130 ? 1 : 5);
  const bool owner = role < 3;
  const int tA = grp * 3;
  int ln_tile, q0, k0, n0, o0, q1 = 0, k1 = 0, n1 = 0, i1 = -1;
  if (cta >= 130) { ln_tile = q0 = 78; k0 = owner ? 0 : 64; n0 = owner ? 64 : NKV - 64; o0 = 78; if (owner) i1 = 78; }
  else if (owner) { ln_tile = q0 = tA + role; k0 = 0; n0 = role == 0 ? SCHED_A : role == 1 ? SCHED_B : SCHED_C; i1 = o0 = q0; }
  else if (role == 3) { ln_tile = q0 = tA + 1; k0 = SCHED_B; n0 = SCHED_B1; o0 = NQT + grp; q1 = tA; k1 = SCHED_A; n1 = NKV - SCHED_A; }
  else { ln_tile = q0 = tA + 2; k0 = SCHED_C; n0 = NKV - SCHED_C; o0 = q0; q1 = tA + 1; k1 = SCHED_B + SCHED_B1; n1 = NKV - k1; i1 = NQT + grp; }
  const bool do_m = role == 0 || role >= 3;

  const bool pub_q = cta < 130 && role < 2;
  const int pub_h = role == 0 ? 3 : owner ? 1 : 2;

  const int wid = threadIdx.x >> 5, xr0 = ln_tile * 128 + wid * 16, xord = owner ? wid : wid ^ 4;
  auto xload = [&]() {
    mbar_expect_tx(xbar0 + 8 * xord, xr0 < N_ ? 8192 : 0);
    if (xr0 < N_) bulk_g2s(sb + SM_Q + wid * 8192, x + (size_t)xr0 * 256, 8192, xbar0 + 8 * xord);
  };
  if (wid < 8 && lane == 0) {
    mbar_init(xbar0 + 8 * xord, 1);
    asm volatile("fence.mbarrier_init.release.cluster;\n" ::: "memory");
    if (xord < XEARLY) xload();
  }
  const int kind = cta >> 5, pd0 = ((cta >> 2) & 7) * 32, pc0 = (cta & 3) * 64;
  if (threadIdx.x == 352) cp16(sb + SM_BAR + 496, &G->epoch);
  if (threadIdx.x == 0) {
    for (int s = 0; s < NST; s++) { mbar_init(full0 + 8 * s, 1); mbar_init(empty0 + 8 * s, 8); }
    for (int i = 0; i < 14; i++) mbar_init(evt0 + 8 * i, 128);
    mbar_init(qbar0, 1); mbar_init(qbar0 + 8, 1);
    mbar_init(hread, 1); mbar_init(auxfree, 1); mbar_init(zready, 32); mbar_init(sbar0, 1); mbar_init(sbar0 + 8, 1);
    mbar_init(wsent, 1); mbar_init(cbar, 384);
    asm volatile("fence.mbarrier_init.release.cluster;\n" ::: "memory");
  }
  if (cta < 96) product_load(kind == 0, kind == 0 ? wq : kind == 1 ? w_msg : wv, kind == 0 ? wk : w_out, pd0, pc0, ring);
  if (threadIdx.x == 256) STAMP(26);

  __syncthreads();
  asm volatile("cp.async.mbarrier.arrive.noinc.shared::cta.b64 [%0];\n" ::"r"(cbar) : "memory");

  if (wg == 2) {
    if (threadIdx.x == 256) STAMP(40);
    mbar_wait(cbar, 0);
    if (cta < 96) {
      PROXY_FENCE_SMEM();
      if (threadIdx.x == 256) STAMP(24);
      product_mma(kind == 0, G->w + kind * 131072, pd0, pc0, ring, &G->ctr[0]);
    }
    asm volatile("setmaxnreg.dec.sync.aligned.u32 40;\n");
    unsigned ep;
    asm volatile("ld.shared.u32 %0, [%1];" : "=r"(ep) : "r"(sb + SM_BAR + 496) : "memory");
    ep += 1;
    const int w = (threadIdx.x >> 5) & 3;
    if (w == 0) {
      if (lane == 0) {
        STAMP(1);
        uint32_t st = 0, ph = 1;
        auto push = [&](const uint8_t* p, uint32_t bytes, bool rem) {
          mbar_wait(empty0 + 8 * st, ph);
          mbar_expect_tx(full0 + 8 * st, rem ? bytes + 8192 : bytes);
          if (bytes) bulk_g2s(ring + st * STB, p, bytes, full0 + 8 * st);
          if (rem) bulk_g2s(sb + SM_REM, p + STB, 8192, full0 + 8 * st);
          if (++st == NST) { st = 0; ph ^= 1; }
        };
        auto qfill = [&](int e, int h, const uint8_t* p, const unsigned* flag, unsigned target, const void* p2, uint32_t dst2, uint32_t bytes2) {
          gwait(flag, target);
          mbar_wait(evt0 + 16 * e + 8 * h, 0);
          PROXY_FENCE_SMEM();
          mbar_expect_tx(qbar0 + 8 * h, 32768 + bytes2);
          bulk_g2s(sb + SM_Q + h * 32768, p + h * 32768, 32768, qbar0 + 8 * h);
          if (bytes2) bulk_g2s(dst2, p2, bytes2, qbar0 + 8 * h);
        };
        auto store = [&](uint8_t* p, uint32_t sm, uint32_t bar) { mbar_wait(bar, 0); bulk_s2g(p, sm, 32768); BULK_COMMIT(); };
        uint8_t* const mp = G->mp + (size_t)ln_tile * 65536;
        gwait(&G->ctr[0], ep * CNT_W);
        PROXY_FENCE_SMEM();
        STAMP(2);
#pragma unroll 1
        for (int i = 0; i < 3; i++) push(G->w + (do_m ? 131072 : 0) + i * STB, STB, i == 2);
        mbar_arrive(wsent);
        if (do_m) {
#pragma unroll 1
          for (int i = 0; i < 3; i++) push(G->w + i * STB, STB, i == 2);
          store(mp, sb + SM_AUX, evt0 + 80);
          BULK_WAIT_READ();
          mbar_arrive(auxfree);
        }
        if (do_m) gwait(&G->ctr[32], ep * CNT_H); else gwait(&G->ctr[128], ep * 5);
        STAMP(3);
        const int ntot = n0 + n1;
#pragma unroll 1
        for (int j = 0; j < ntot + 3; j++) {
          if (j == 3) gwait(&G->ctr[32], ep * CNT_H);
          if (j < ntot) push(G->ht + (size_t)(j >= n0 ? k1 + j - n0 : j >= 5 ? k0 + j : j < 3 ? k0 + j + 2 : k0 + j - 3) * STB, STB, false);
          else if (owner) {
            if (j == ntot) {
              gwait(&G->ctr[96], ep * CNT_G);
              const bool tl = q0 == NQT - 1;
              mbar_expect_tx(wsent, tl ? 8192 + 32 : 32768 + 256);
              bulk_g2s(sb + SM_AUX, x + (size_t)q0 * 32768, tl ? 8192 : 32768, wsent);
              bulk_g2s(sb + SM_BAR + 512, deg_inv + q0 * 128, tl ? 32 : 256, wsent);
            }
            push(G->w + 262144 + (j - ntot) * STB, STB, j == ntot + 2);
          }
          if (j == 2) {
#pragma unroll 1
            for (int h = 0; h < 2; h++) {
              if (pub_q) { store(G->qt + (size_t)q0 * 65536 + h * 32768, sb + SM_Q + h * 32768, evt0 + 8 * h); BULK_WAIT_READ(); }
              mbar_arrive(qbar0 + 8 * h);
            }
          }
          if (j == 3 && do_m) store(mp + 32768, sb + SM_AUX, evt0 + 8);
          if (j == 4) {
            mbar_wait(zready, 0);
#pragma unroll 1
            for (int i = 0; i < 5; i++) bulk_s2g(G->acc + (size_t)cta * 40960 + i * 8192, sb + SM_REM, 8192);
            BULK_COMMIT();
            BULK_WAIT();
            garrive_bulk(&G->ctr[64]);
          }
          if (n1) {
            const int h = j - n0;
            if (h == 0 || h == 1) qfill(1, h, G->qt + (size_t)q1 * 65536, &G->ctr[64], ep * CNT_M, nullptr, 0, 0);
            if (h == 2) { mbar_wait(evt0 + 32, 0); mbar_wait(evt0 + 40, 0); GPU_FENCE(); gset(&G->pflag[o0 * 2], ep); gset(&G->pflag[o0 * 2 + 1], ep); }
          }
          const int h = j - ntot;
          if ((h == 0 || h == 1) && i1 >= 0)
            qfill(n1 ? 6 : 1, h, G->part + (size_t)i1 * 65536, &G->pflag[i1 * 2 + h], ep, &G->meta[i1 * 128 + h * 64], sb + SM_META + h * 512, 512);
        }
#pragma unroll 1
        for (int u = 0; u < 2; u++) {
          if (owner) qfill(2, u, G->acc + (size_t)q0 * 65536, &G->ctr[96], ep * CNT_G, nullptr, 0, 0);
          else {
            const int slot = n1 ? q1 : o0;
            mbar_wait(evt0 + 48 + 8 * u, 0);
            bulk_s2g(G->part + (size_t)slot * 65536 + u * 32768, sb + SM_Q + u * 32768, 32768);
            bulk_s2g(&G->meta[slot * 128 + u * 64], sb + SM_META + u * 512, 512);
            BULK_COMMIT();
            BULK_WAIT();
            gset(&G->pflag[slot * 2 + u], ep);
          }
        }
        if (owner) push((const uint8_t*)x + (size_t)q0 * 65536 + 32768, q0 == NQT - 1 ? 0 : 32768, false);
        if (cta == 0) G->epoch = ep;
      }
    } else if (w == 3) {
      if (lane == 0) {
        mbar_wait(wsent, 0);
#pragma unroll 1
        for (int h = 0; h < 2; h++)
          if (pub_h >> h & 1) { mbar_wait(evt0 + 64 + 8 * h, 0); bulk_s2g(G->ht + (size_t)ln_tile * 65536 + h * 32768, sb + SM_Q + h * 32768, 32768); BULK_COMMIT(); }
        if (cta >= 1 && cta <= 5) {
          if (cta == 5) asm volatile("cp.async.bulk.wait_group 1;\n" ::: "memory"); else BULK_WAIT();
          garrive_bulk(&G->ctr[128]);
        }
        BULK_WAIT();
        garrive_bulk(&G->ctr[32]);
        mbar_arrive(hread);
        STAMP(30);
      }
      __syncwarp();
      mbar_wait(evt0, 0);
      mbar_wait(evt0 + 8, 0);
#pragma unroll 4
      for (int i = 0; i < 16; i++) sts128(sb + SM_REM + i * 512 + lane * 16, 0, 0, 0, 0);
      PROXY_FENCE_SMEM();
      mbar_arrive(zready);
    } else {
      int b = cta * 2 + w - 1;
      int es = __ldg(src + b * 32 + lane), ed = __ldg(dst + b * 32 + lane);
      mbar_wait(zready, 0);
      __nanosleep(3000);
      if (lane == 0) gwait(&G->ctr[64], ep * CNT_M);
      PROXY_FENCE_SMEM();
      __syncwarp();
      if (w == 1 && lane == 0) STAMP(4);
      const uint32_t sbar = sbar0 + 8 * (w - 1), slot = sb + SM_AUX + (w - 1) * 16384 + lane * 512;
      uint32_t ph = 0;
#pragma unroll 1
      while (b < E_ / 32) {
        if (lane == 0) mbar_expect_tx(sbar, 16384);
        __syncwarp();
        bulk_g2s(slot, G->mp + (size_t)es * 512, 512, sbar);
        uint8_t* dp = G->acc + (size_t)ed * 512;
        b += NCTA * 2;
        if (b < E_ / 32) { es = __ldg(src + b * 32 + lane); ed = __ldg(dst + b * 32 + lane); }
        mbar_wait(sbar, ph);
        ph ^= 1;
        asm volatile("cp.reduce.async.bulk.global.shared::cta.bulk_group.add.noftz.bf16 [%0], [%1], 512;\n" ::"l"(dp), "r"(slot) : "memory");
        BULK_COMMIT();
        BULK_WAIT_READ();
      }
      BULK_WAIT();
      __syncwarp();
      if (lane == 0) garrive(&G->ctr[96]);
      if (w == 1 && lane == 0) STAMP(5);
    }
  } else {
    const int g = lane >> 2, t = lane & 3, wp = __shfl_sync(~0u, (threadIdx.x >> 5) & 3, 0), tid = threadIdx.x & 127;
    const uint32_t qh = sb + SM_Q + wg * 32768;
    const uint32_t qw = qh + wp * 8192;
    const uint32_t qbar = qbar0 + 8 * wg;
    auto event = [&](int e) { mbar_arrive(evt0 + 16 * e + 8 * wg); };
    if (wg == 1) bar_arrive(1, 256);
    {
      const bool valid = xr0 < N_;
      if (xord >= XDEPTH) mbar_wait(xbar0 + 8 * (xord - XDEPTH), 0);
      if (lane == 0 && xord >= XEARLY) xload();
      if (threadIdx.x == 0) STAMP(35);
      mbar_wait(xbar0 + 8 * xord, 0);
      if (threadIdx.x == 0) STAMP(25);
      if (threadIdx.x == 224) STAMP(41);
      uint4 xa[8], xb[8];
      const uint32_t sw = (g & 1) << 6;
#pragma unroll
      for (int J = 0; J < 8; J++) {
        xa[J] = xb[J] = make_uint4(0, 0, 0, 0);
        if (valid) { xa[J] = lds128(qw + g * 512 + t * 16 + ((J * 64) ^ sw)); xb[J] = lds128(qw + 4096 + g * 512 + t * 16 + ((J * 64) ^ sw)); }
      }
      __syncwarp();
      if (threadIdx.x == 0 && xb[7].w != 0x12345) STAMP(36);
      float sm[2][4] = {}, qa[2][4] = {}, qb[2][4] = {};
#pragma unroll
      for (int J = 0; J < 8; J++)
#pragma unroll
        for (int i = 0; i < 4; i += 2) {
          const uint32_t a0 = comp(xa[J], i), a1 = comp(xb[J], i), a2 = comp(xa[J], i + 1), a3 = comp(xb[J], i + 1);
          mma16816(sm[i >> 1], a0, a1, a2, a3, 0x3f803f80u, 0x3f803f80u);
          mma16816(qa[i >> 1], a0, a1, a2, a3, a0, a2);
          mma16816(qb[i >> 1], a0, a1, a2, a3, a1, a3);
        }
      const int dl = (lane & 28) | (g >> 1);
      const float ssa = __shfl_sync(~0u, (g & 1) ? qa[0][1] + qa[1][1] : qa[0][0] + qa[1][0], dl);
      const float ssb = __shfl_sync(~0u, (g & 1) ? qb[0][3] + qb[1][3] : qb[0][2] + qb[1][2], dl);
      if (threadIdx.x == 0 && ssb != 123.f && ssa != 123.f) STAMP(37);
      const uint32_t wa = qw + g * 128 + (((t ^ g) << 4) ^ sw);
#pragma unroll
      for (int rr = 0; rr < 2; rr++) {
        const float mean = (sm[0][2 * rr] + sm[1][2 * rr]) * (1.f / 256.f);
        const float rstd = rsqrtf(fmaxf(fmaf(-mean, mean, (rr ? ssb : ssa) * (1.f / 256.f)), 0.f) + 1e-5f);
#pragma unroll
        for (int J = 0; J < 8; J++) {
          const uint4 v = rr ? xb[J] : xa[J];
          float c = mean;
          const bool lastc = J >= 6 && (lane & 7) == (J == 7 ? 3 : 7);
          if (lastc) c = bhi(v.w);
          c *= -rstd;
          uint32_t r3 = pack2(fmaf(blo(v.w), rstd, c), fmaf(bhi(v.w), rstd, c));
          if (lastc) r3 = (r3 & 0xffffu) | 0x3f800000u;
          sts128((wa ^ ((J & 1) << 6)) + rr * 4096 + (J >> 1) * 1024, pack2(fmaf(blo(v.x), rstd, c), fmaf(bhi(v.x), rstd, c)),
                 pack2(fmaf(blo(v.y), rstd, c), fmaf(bhi(v.y), rstd, c)), pack2(fmaf(blo(v.z), rstd, c), fmaf(bhi(v.z), rstd, c)), r3);
        }
      }
      if (threadIdx.x == 0) STAMP(38);
      PROXY_FENCE_SMEM();
      if (threadIdx.x == 0) STAMP(39);
    }
    event(4);
    bar_sync(3 + wg, 128);
    if (tid == 0) STAMP(wg ? 42 : 6);
    asm volatile("setmaxnreg.inc.sync.aligned.u32 232;\n");

    float o[128];
    uint32_t ga[64];
    uint32_t st = 0, ph = 0, pst = 0;
    const uint32_t qd = mkdesc(qh, 16), kd0 = mkdesc(ring, 16), vd0 = mkdesc(ring, 1024), rd = mkdesc(sb + SM_REM, 1024);
    auto wait_full = [&]() { mbar_wait(full0 + 8 * st, ph); };
    auto advance = [&]() { pst = st; if (++st == NST) { st = 0; ph ^= 1; } };
    auto release = [&]() { if (lane == 0) mbar_arrive(empty0 + 8 * pst); };

#pragma unroll 1
    for (int job = do_m ? 0 : 1; job < 2; job++) {
      wait_full();
      bar_sync(1 + wg, 256);
#pragma unroll
      for (int c = 0; c < 3; c++) {
        if (c) wait_full();
        if (threadIdx.x == 0 && c == 0 && ph == 0) STAMP(28);
        WG_FENCE();
#pragma unroll
        for (int k = 0; k < 5; k++) { const int ks = c * 5 + k; wgmma_ss256(o, qd + (ks >> 2) * 64 + (ks & 3) * 2, vd0 + c * (STB >> 4) + k * 512, ks != 0); }
        if (c == 2) wgmma_ss256(o, qd + 3 * 64 + 6, rd, 1);
        WG_COMMIT();
        if (c == 2) bar_arrive(2 - wg, 256);
        if (c > 0) { WG_WAIT(1); release(); }
        advance();
      }
      WG_WAIT(0);
      pin(o);
      release();
      if (threadIdx.x == 0) STAMP(29);
      if (job == 0) {
#pragma unroll
        for (int i = 0; i < 64; i++) ga[i] = pack2(o[2 * i], o[2 * i + 1]);
      } else {
        mbar_wait(hread, 0);
        bar_sync(3 + wg, 128);
        if (threadIdx.x == 0) STAMP(45);
        const uint32_t sa = qw + ((lane >> 3) & 1) * 4096 + (lane & 7) * 128 + (((lane >> 4) ^ (lane & 7)) << 4);
#pragma unroll
        for (int i = 0; i < 32; i += 2)
          stsm4((sa ^ ((i & 7) << 4)) + (i >> 3) * 1024, pack2(o[4 * i], o[4 * i + 1]), pack2(o[4 * i + 2], o[4 * i + 3]), pack2(o[4 * i + 4], o[4 * i + 5]), pack2(o[4 * i + 6], o[4 * i + 7]));
        if (threadIdx.x == 0) STAMP(46);
      }
      if (do_m && job == wg) {
        if (wg) mbar_wait(auxfree, 0);
        const uint32_t ma = sb + SM_AUX + wp * 8192 + g * 512 + t * 16;
#pragma unroll
        for (int J = 0; J < 8; J++) {
          sts128(ma + J * 64, ga[8 * J], ga[8 * J + 2], ga[8 * J + 4], ga[8 * J + 6]);
          sts128(ma + 4096 + J * 64, ga[8 * J + 1], ga[8 * J + 3], ga[8 * J + 5], ga[8 * J + 7]);
        }
      }
      PROXY_FENCE_SMEM();
      event(job ? 0 : 5);
    }
    if (threadIdx.x == 0) STAMP(7);

    float s[BN / 2];
    uint32_t p[BN / 4];
    float m0, m1, mb0, mb1, l0, l1;
    const uint32_t qcol = qw + g * 128 + 3 * 1024 + ((7 ^ g) << 4) + 14;
    auto qk = [&]() {
      const uint32_t kd = kd0 + st * (STB >> 4);
#pragma unroll
      for (int ks = 0; ks < 16; ks++) { const uint32_t off = (ks >> 2) * 64 + (ks & 3) * 2; wgmma_qk(s, qd + off, kd + off, ks > 0); }
      WG_COMMIT();
    };
    auto pv = [&]() {
      const uint32_t vd = vd0 + pst * (STB >> 4);
#pragma unroll
      for (int ks = 0; ks < BN / 16; ks++) wgmma_rs256(o, p[ks * 4], p[ks * 4 + 1], p[ks * 4 + 2], p[ks * 4 + 3], vd + ks * 512, 1);
      WG_COMMIT();
    };
    auto softmax_slow = [&](bool store) {
      float x0 = fmaxf(s[0], s[1]), x1 = fmaxf(s[2], s[3]);
#pragma unroll
      for (int i = 1; i < BN / 8; i++) { x0 = fmaxf(x0, fmaxf(s[4 * i], s[4 * i + 1])); x1 = fmaxf(x1, fmaxf(s[4 * i + 2], s[4 * i + 3])); }
      float r0 = fmaxf(m0, ceilf(quad_max(x0) + mb0 + 32.f)), r1 = fmaxf(m1, ceilf(quad_max(x1) + mb1 + 32.f));
      uint32_t pk = pack2(r0, r1);
      const float b0 = blo(pk), b1 = bhi(pk);
      const bool ok0 = fabsf(b0 - r0) <= 8.f, ok1 = fabsf(b1 - r1) <= 8.f;
      if (ok0) r0 = b0;
      if (ok1) r1 = b1;
      const float a0 = ex2(m0 - r0), a1 = ex2(m1 - r1), d0 = r0 - mb0, d1 = r1 - mb1;
      m0 = r0; m1 = r1;
      if (store) { mb0 = b0; mb1 = b1; }
      if (t == 3 && store) {
        pk ^= 0x80008000u;
        asm volatile("st.shared.u16 [%0], %1;\n" ::"r"(qcol), "h"((unsigned short)(pk & 0xffff)) : "memory");
        asm volatile("st.shared.u16 [%0], %1;\n" ::"r"(qcol + 4096), "h"((unsigned short)(pk >> 16)) : "memory");
      }
      PROXY_FENCE_SMEM();
#pragma unroll
      for (int i = 0; i < 32; i++) { o[4 * i] *= a0; o[4 * i + 1] *= a0; o[4 * i + 2] *= a1; o[4 * i + 3] *= a1; }
#pragma unroll
      for (int i = 0; i < BN / 8; i++) {
        p[2 * i] = pack2(ex2(s[4 * i] - d0), ex2(s[4 * i + 1] - d0));
        p[2 * i + 1] = pack2(ex2(s[4 * i + 2] - d1), ex2(s[4 * i + 3] - d1));
      }
      return (bool)__any_sync(~0u, !(ok0 && ok1 && store));
    };
#pragma unroll 1
    for (int seg = 0;; seg++) {
      int left = (seg ? n1 : n0) - 1;
      if (seg) mbar_wait(qbar, 1);
      wait_full();
      bar_sync(1 + wg, 256);
      WG_FENCE();
      qk();
      bar_arrive(2 - wg, 256);
      m0 = m1 = -INFINITY;
      mb0 = mb1 = 0.f;
#pragma unroll
      for (int i = 0; i < 128; i++) o[i] = 0.f;
      WG_WAIT(0);
      pin(s);
      if (threadIdx.x == 0) STAMP(8 + seg);
      bool slow = softmax_slow(seg || mbar_test(qbar, 0));
      advance();
#pragma unroll 1
      do {
        wait_full();
        bar_sync(1 + wg, 256);
        WG_FENCE();
        pv();
        qk();
        bar_arrive(2 - wg, 256);
        WG_WAIT(1);
        release();
        WG_WAIT(0);
        pin(s); pin(o);
        left--;
        if (left == 0) event(seg ? 6 : 1);
        if (!slow) {
          uint32_t acc = 0;
#pragma unroll
          for (int i = 0; i < BN / 4; i++) { p[i] = pack2(ex2(s[2 * i]), ex2(s[2 * i + 1])); acc |= p[i]; }
          slow = __any_sync(~0u, (acc & 0x40004000u) != 0);
        }
        if (slow) slow = softmax_slow(left != 0 && (seg || mbar_test(qbar, 0)));
        advance();
      } while (left);
      bar_sync(1 + wg, 256);
      WG_FENCE();
      pv();
      bar_arrive(2 - wg, 256);
      WG_WAIT(0);
      pin(o);
      release();
      if (tid == 0) STAMP(10 + seg * 2 + wg);
      const bool lastseg = seg || !n1, merge = lastseg && i1 >= 0;
      const uint32_t ma = sb + SM_META + wg * 512 + (wp * 16 + g) * 8;
      uint32_t bb0 = 0, bb1 = 0;
      l0 = l1 = 0.f;
      if (merge) {
        mbar_wait(qbar, seg ^ 1);
        if (tid == 0) STAMP(18 + wg);
        float2 h0, h1;
        asm volatile("ld.shared.v2.f32 {%0,%1}, [%2];" : "=f"(h0.x), "=f"(h0.y) : "r"(ma) : "memory");
        asm volatile("ld.shared.v2.f32 {%0,%1}, [%2];" : "=f"(h1.x), "=f"(h1.y) : "r"(ma + 64) : "memory");
        if (__any_sync(~0u, h0.x - m0 > 20.f || h1.x - m1 > 20.f)) {
          const float t0 = fmaxf(m0, h0.x), t1 = fmaxf(m1, h1.x), a0 = ex2(m0 - t0), a1 = ex2(m1 - t1);
          m0 = t0; m1 = t1;
#pragma unroll
          for (int i = 0; i < 32; i++) { o[4 * i] *= a0; o[4 * i + 1] *= a0; o[4 * i + 2] *= a1; o[4 * i + 3] *= a1; }
        }
        const float b0 = ex2(h0.x - m0), b1 = ex2(h1.x - m1);
        l0 = b0 * h0.y; l1 = b1 * h1.y;
        bb0 = pack2(b0, b0); bb1 = pack2(b1, b1);
      }
      l0 += __shfl_sync(~0u, o[125], lane | 3);
      l1 += __shfl_sync(~0u, o[127], lane | 3);
#pragma unroll
      for (int k = 0; k < 16; k++) {
        uint4 v = make_uint4(0, 0, 0, 0);
        if (merge) v = lds128(qh + k * 2048 + tid * 16);
        ga[4 * k] = hfma2(v.x, bb0, pack2(o[8 * k], o[8 * k + 1]));
        ga[4 * k + 1] = hfma2(v.y, bb1, pack2(o[8 * k + 2], o[8 * k + 3]));
        ga[4 * k + 2] = hfma2(v.z, bb0, pack2(o[8 * k + 4], o[8 * k + 5]));
        ga[4 * k + 3] = hfma2(v.w, bb1, pack2(o[8 * k + 6], o[8 * k + 7]));
      }
      if (lastseg) break;
      uint8_t* pp = G->part + (size_t)o0 * 65536 + wg * 32768 + tid * 16;
#pragma unroll
      for (int k = 0; k < 16; k++) stg128(pp + k * 2048, ga[4 * k], ga[4 * k + 1], ga[4 * k + 2], ga[4 * k + 3]);
      if (t == 0) {
        G->meta[o0 * 128 + wg * 64 + wp * 16 + g] = make_float2(m0, l0);
        G->meta[o0 * 128 + wg * 64 + wp * 16 + g + 8] = make_float2(m1, l1);
      }
      event(2);
      if (tid == 0) STAMP(14 + wg);
    }

    if (!owner) {
#pragma unroll
      for (int k = 0; k < 16; k++) sts128(qh + k * 2048 + tid * 16, ga[4 * k], ga[4 * k + 1], ga[4 * k + 2], ga[4 * k + 3]);
      if (t == 0) {
        const uint32_t ma = sb + SM_META + wg * 512 + (wp * 16 + g) * 8;
        asm volatile("st.shared.v2.f32 [%0], {%1,%2};" ::"r"(ma), "f"(m0), "f"(l0) : "memory");
        asm volatile("st.shared.v2.f32 [%0], {%1,%2};" ::"r"(ma + 64), "f"(m1), "f"(l1) : "memory");
      }
      PROXY_FENCE_SMEM();
      event(3);
      if (tid == 0) STAMP(16 + wg);
      if (wg == 0) bar_sync(1, 256);
    } else {
      const int r0 = q0 * 128 + wg * 64 + wp * 16;
      const bool valid = r0 < N_;
      const float il0 = rcp(l0), il1 = rcp(l1);
#pragma unroll
      for (int i = 0; i < 64; i++) asm volatile("" : "+r"(ga[i])::"memory");
      event(2);
      if (tid == 0) STAMP(47 + wg);
      bar_sync(1 + wg, 256);
#pragma unroll
      for (int c = 0; c < 3; c++) {
        wait_full();
        WG_FENCE();
        const uint32_t wd = vd0 + st * (STB >> 4);
#pragma unroll
        for (int k = 0; k < 5; k++) { const int ks = c * 5 + k; wgmma_rs256(o, ga[ks * 4], ga[ks * 4 + 1], ga[ks * 4 + 2], ga[ks * 4 + 3], wd + k * 512, ks != 0); }
        if (c == 2) wgmma_rs256(o, ga[60], ga[61], ga[62], ga[63], rd, 1);
        WG_COMMIT();
        if (c == 1) { WG_WAIT(1); release(); }
        advance();
      }
      if (wg == 0) bar_arrive(2, 256);
      WG_WAIT(0);
      pin(o);
      if (tid == 0) STAMP(49 + wg);
      mbar_wait(wsent, 1);
      mbar_wait(qbar, 0);
      if (wg == 1) wait_full();
      if (tid == 0) STAMP(20 + wg);
      const uint32_t ro = g * 512 + t * 16 + ((g & 1) << 6);
      const uint32_t ap = qw + ro, xp = (wg ? ring + st * STB : sb + SM_AUX) + wp * 8192 + ro;
      const bool odd = g & 1;
#pragma unroll
      for (int h = 0; h < 2; h++) {
        uint4 av[8], xv[8];
#pragma unroll
        for (int J = 0; J < 8; J++) { av[J] = lds128((ap ^ ((J & 1) << 6)) + h * 4096 + (J >> 1) * 128); xv[J] = lds128((xp ^ ((J & 1) << 6)) + h * 4096 + (J >> 1) * 128); }
        const float il = h ? il1 : il0;
        uint32_t di;
        asm volatile("ld.shared.u16 %0, [%1];" : "=r"(di) : "r"(sb + SM_BAR + 512 + (wg * 64 + wp * 16 + h * 8 + g) * 2) : "memory");
        di *= 0x10001u;
#pragma unroll
        for (int J = 0; J < 8; J += 2) {
          uint32_t y[8];
#pragma unroll
          for (int i = 0; i < 8; i++) y[i] = pack2(o[16 * J + 4 * i + 2 * h] * il, o[16 * J + 4 * i + 2 * h + 1] * il);
#pragma unroll
          for (int u = 0; u < 2; u++) {
            uint32_t r[4];
#pragma unroll
            for (int i = 0; i < 4; i++) r[i] = hadd2(comp(xv[J + u], i), hfma2(comp(av[J + u], i), di, odd ? y[(u ^ 1) * 4 + i] : y[u * 4 + i]));
            sts128((ap ^ (u << 6)) + h * 4096 + J * 64, r[0], r[1], r[2], r[3]);
          }
        }
        PROXY_FENCE_SMEM();
        __syncwarp();
        if (lane == 0 && valid) { bulk_s2g((uint8_t*)out + (size_t)r0 * 512 + h * 4096, qw + h * 4096, 4096); BULK_COMMIT(); }
      }
      if (tid == 0) STAMP(51 + wg);
      BULK_WAIT_READ();
      if (tid == 0) STAMP(22 + wg);
    }
    PROF_DUMP();
  }
}

}

extern "C" void kernel_launch(void* const* d_in, const int* in_sizes, int n_in, void* d_out, int out_size) {
  (void)in_sizes; (void)n_in; (void)out_size;
  void* scratch = nullptr;
  cudaGetSymbolAddress(&scratch, g_scratch);
  cudaFuncSetAttribute(gps_kernel, cudaFuncAttributeMaxDynamicSharedMemorySize, SM_TOTAL);
  gps_kernel<<<NCTA, 384, SM_TOTAL>>>((const __nv_bfloat16*)d_in[0], (const int*)d_in[1], (const int*)d_in[2],
                                      (const __nv_bfloat16*)d_in[3], (const __nv_bfloat16*)d_in[4], (const __nv_bfloat16*)d_in[5],
                                      (const __nv_bfloat16*)d_in[6], (const __nv_bfloat16*)d_in[7], (const __nv_bfloat16*)d_in[8],
                                      (__nv_bfloat16*)d_out, (Scratch*)scratch);
}
```

```cpp
#include <cuda_runtime.h>
#include <cuda_bf16.h>
#include <stdint.h>

namespace {

constexpr int N_ = 10000, E_ = 160000, NQT = 79, NPAD = NQT * 128;
constexpr int BN = 80, NKV = 125, NST = 3, STB = BN * 512, NCTA = 132;
constexpr int NSLOT = NQT + 26;
#define SCHED_A 76
#define SCHED_B 76
#define SCHED_C 76
#define SCHED_B1 25
#define NQR 1
#define JBG 5
#define JSCAT 45
constexpr int SM_Q = 0, SM_RING = 65536, SM_REM = SM_RING + NST * STB, SM_AUX = SM_REM + 8192, SM_META = SM_AUX + 32768;
constexpr int SM_BAR = SM_META + 1024, SM_DINV = SM_BAR + 1280, SM_TOTAL = SM_BAR + 1792;
constexpr unsigned CNT_W = 64, CNT_H = NCTA, CNT_E = 5, CNT_F = 4, CNT_M = NCTA + 64, CNT_G = NCTA * 2;
constexpr int C_W = 0, C_H = 32, C_E = 64, C_M = 96, C_G = 128, C_F = 160;

struct Scratch {
  unsigned ctr[6 * 32], epoch, pad0[31], pflag[NSLOT * 2], pad1[1024 - 7 * 32 - NSLOT * 2];
  uint8_t w[3 * 131072];
  float2 meta[NSLOT * 128];
  uint8_t ht[NPAD * 512];
  uint8_t qt[NPAD * 512];
  uint8_t acc[NCTA * 40960];
  uint8_t part[NSLOT * 65536];
  unsigned box[NCTA * NKV * 32];
  int ovf[NCTA * 1280];
};
__device__ __align__(1024) Scratch g_scratch;
#define STAMPIF(c, i)
#define GSTAMPIF(c, i)
#define PROF_DUMP()

constexpr uint32_t DESC_HI = 0x40000100u;
__device__ __forceinline__ void wgmma_qk64(float (&d)[40], uint64_t da, uint64_t db, int sd) {
  asm volatile("{\n.reg .pred p;\nsetp.ne.b32 p, %42, 0;\n"
    "wgmma.mma_async.sync.aligned.m64n80k16.f32.bf16.bf16 {%0, %1, %2, %3, %4, %5, %6, %7, %8, %9, %10, %11, %12, %13, %14, %15, %16, %17, %18, %19, %20, %21, %22, %23, %24, %25, %26, %27, %28, %29, %30, %31, %32, %33, %34, %35, %36, %37, %38, %39}, %40, %41, p, 1, 1, 0, 0;\n}\n"
    : "+f"(d[0]), "+f"(d[1]), "+f"(d[2]), "+f"(d[3]), "+f"(d[4]), "+f"(d[5]), "+f"(d[6]), "+f"(d[7]), "+f"(d[8]), "+f"(d[9]), "+f"(d[10]), "+f"(d[11]), "+f"(d[12]), "+f"(d[13]), "+f"(d[14]), "+f"(d[15]), "+f"(d[16]), "+f"(d[17]), "+f"(d[18]), "+f"(d[19]), "+f"(d[20]), "+f"(d[21]), "+f"(d[22]), "+f"(d[23]), "+f"(d[24]), "+f"(d[25]), "+f"(d[26]), "+f"(d[27]), "+f"(d[28]), "+f"(d[29]), "+f"(d[30]), "+f"(d[31]), "+f"(d[32]), "+f"(d[33]), "+f"(d[34]), "+f"(d[35]), "+f"(d[36]), "+f"(d[37]), "+f"(d[38]), "+f"(d[39])
    : "l"(da), "l"(db), "r"(sd));
}

__device__ __forceinline__ void wgmma_qkr64(float (&d)[40], uint32_t a0, uint32_t a1, uint32_t a2, uint32_t a3, uint64_t db, int sd) {
  asm volatile("{\n.reg .pred p;\nsetp.ne.b32 p, %45, 0;\n"
    "wgmma.mma_async.sync.aligned.m64n80k16.f32.bf16.bf16 {%0, %1, %2, %3, %4, %5, %6, %7, %8, %9, %10, %11, %12, %13, %14, %15, %16, %17, %18, %19, %20, %21, %22, %23, %24, %25, %26, %27, %28, %29, %30, %31, %32, %33, %34, %35, %36, %37, %38, %39}, {%40, %41, %42, %43}, %44, p, 1, 1, 0;\n}\n"
    : "+f"(d[0]), "+f"(d[1]), "+f"(d[2]), "+f"(d[3]), "+f"(d[4]), "+f"(d[5]), "+f"(d[6]), "+f"(d[7]), "+f"(d[8]), "+f"(d[9]), "+f"(d[10]), "+f"(d[11]), "+f"(d[12]), "+f"(d[13]), "+f"(d[14]), "+f"(d[15]), "+f"(d[16]), "+f"(d[17]), "+f"(d[18]), "+f"(d[19]), "+f"(d[20]), "+f"(d[21]), "+f"(d[22]), "+f"(d[23]), "+f"(d[24]), "+f"(d[25]), "+f"(d[26]), "+f"(d[27]), "+f"(d[28]), "+f"(d[29]), "+f"(d[30]), "+f"(d[31]), "+f"(d[32]), "+f"(d[33]), "+f"(d[34]), "+f"(d[35]), "+f"(d[36]), "+f"(d[37]), "+f"(d[38]), "+f"(d[39])
    : "r"(a0), "r"(a1), "r"(a2), "r"(a3), "l"(db), "r"(sd));
}

__device__ __forceinline__ void wgmma_pv64(float (&d)[128], uint32_t a0, uint32_t a1, uint32_t a2, uint32_t a3, uint64_t db, int sd) {
  asm volatile("{\n.reg .pred p;\nsetp.ne.b32 p, %133, 0;\n"
    "wgmma.mma_async.sync.aligned.m64n256k16.f32.bf16.bf16 {%0, %1, %2, %3, %4, %5, %6, %7, %8, %9, %10, %11, %12, %13, %14, %15, %16, %17, %18, %19, %20, %21, %22, %23, %24, %25, %26, %27, %28, %29, %30, %31, %32, %33, %34, %35, %36, %37, %38, %39, %40, %41, %42, %43, %44, %45, %46, %47, %48, %49, %50, %51, %52, %53, %54, %55, %56, %57, %58, %59, %60, %61, %62, %63, %64, %65, %66, %67, %68, %69, %70, %71, %72, %73, %74, %75, %76, %77, %78, %79, %80, %81, %82, %83, %84, %85, %86, %87, %88, %89, %90, %91, %92, %93, %94, %95, %96, %97, %98, %99, %100, %101, %102, %103, %104, %105, %106, %107, %108, %109, %110, %111, %112, %113, %114, %115, %116, %117, %118, %119, %120, %121, %122, %123, %124, %125, %126, %127}, {%128, %129, %130, %131}, %132, p, 1, 1, 1;\n}\n"
    : "+f"(d[0]), "+f"(d[1]), "+f"(d[2]), "+f"(d[3]), "+f"(d[4]), "+f"(d[5]), "+f"(d[6]), "+f"(d[7]), "+f"(d[8]), "+f"(d[9]), "+f"(d[10]), "+f"(d[11]), "+f"(d[12]), "+f"(d[13]), "+f"(d[14]), "+f"(d[15]), "+f"(d[16]), "+f"(d[17]), "+f"(d[18]), "+f"(d[19]), "+f"(d[20]), "+f"(d[21]), "+f"(d[22]), "+f"(d[23]), "+f"(d[24]), "+f"(d[25]), "+f"(d[26]), "+f"(d[27]), "+f"(d[28]), "+f"(d[29]), "+f"(d[30]), "+f"(d[31]), "+f"(d[32]), "+f"(d[33]), "+f"(d[34]), "+f"(d[35]), "+f"(d[36]), "+f"(d[37]), "+f"(d[38]), "+f"(d[39]), "+f"(d[40]), "+f"(d[41]), "+f"(d[42]), "+f"(d[43]), "+f"(d[44]), "+f"(d[45]), "+f"(d[46]), "+f"(d[47]), "+f"(d[48]), "+f"(d[49]), "+f"(d[50]), "+f"(d[51]), "+f"(d[52]), "+f"(d[53]), "+f"(d[54]), "+f"(d[55]), "+f"(d[56]), "+f"(d[57]), "+f"(d[58]), "+f"(d[59]), "+f"(d[60]), "+f"(d[61]), "+f"(d[62]), "+f"(d[63]), "+f"(d[64]), "+f"(d[65]), "+f"(d[66]), "+f"(d[67]), "+f"(d[68]), "+f"(d[69]), "+f"(d[70]), "+f"(d[71]), "+f"(d[72]), "+f"(d[73]), "+f"(d[74]), "+f"(d[75]), "+f"(d[76]), "+f"(d[77]), "+f"(d[78]), "+f"(d[79]), "+f"(d[80]), "+f"(d[81]), "+f"(d[82]), "+f"(d[83]), "+f"(d[84]), "+f"(d[85]), "+f"(d[86]), "+f"(d[87]), "+f"(d[88]), "+f"(d[89]), "+f"(d[90]), "+f"(d[91]), "+f"(d[92]), "+f"(d[93]), "+f"(d[94]), "+f"(d[95]), "+f"(d[96]), "+f"(d[97]), "+f"(d[98]), "+f"(d[99]), "+f"(d[100]), "+f"(d[101]), "+f"(d[102]), "+f"(d[103]), "+f"(d[104]), "+f"(d[105]), "+f"(d[106]), "+f"(d[107]), "+f"(d[108]), "+f"(d[109]), "+f"(d[110]), "+f"(d[111]), "+f"(d[112]), "+f"(d[113]), "+f"(d[114]), "+f"(d[115]), "+f"(d[116]), "+f"(d[117]), "+f"(d[118]), "+f"(d[119]), "+f"(d[120]), "+f"(d[121]), "+f"(d[122]), "+f"(d[123]), "+f"(d[124]), "+f"(d[125]), "+f"(d[126]), "+f"(d[127])
    : "r"(a0), "r"(a1), "r"(a2), "r"(a3), "l"(db), "r"(sd));
}

__device__ __forceinline__ void wgmma_qk(float (&d)[40], uint32_t da, uint32_t db, int sd) {
  asm volatile("{\n.reg .pred p;\n.reg .b64 da, db;\nmov.b64 da, {%40, %43};\nmov.b64 db, {%41, %43};\nsetp.ne.b32 p, %42, 0;\n"
    "wgmma.mma_async.sync.aligned.m64n80k16.f32.bf16.bf16 {%0, %1, %2, %3, %4, %5, %6, %7, %8, %9, %10, %11, %12, %13, %14, %15, %16, %17, %18, %19, %20, %21, %22, %23, %24, %25, %26, %27, %28, %29, %30, %31, %32, %33, %34, %35, %36, %37, %38, %39}, da, db, p, 1, 1, 0, 0;\n}\n"
    : "+f"(d[0]), "+f"(d[1]), "+f"(d[2]), "+f"(d[3]), "+f"(d[4]), "+f"(d[5]), "+f"(d[6]), "+f"(d[7]), "+f"(d[8]), "+f"(d[9]), "+f"(d[10]), "+f"(d[11]), "+f"(d[12]), "+f"(d[13]), "+f"(d[14]), "+f"(d[15]), "+f"(d[16]), "+f"(d[17]), "+f"(d[18]), "+f"(d[19]), "+f"(d[20]), "+f"(d[21]), "+f"(d[22]), "+f"(d[23]), "+f"(d[24]), "+f"(d[25]), "+f"(d[26]), "+f"(d[27]), "+f"(d[28]), "+f"(d[29]), "+f"(d[30]), "+f"(d[31]), "+f"(d[32]), "+f"(d[33]), "+f"(d[34]), "+f"(d[35]), "+f"(d[36]), "+f"(d[37]), "+f"(d[38]), "+f"(d[39])
    : "r"(da), "r"(db), "r"(sd), "r"(DESC_HI));
}

__device__ __forceinline__ void wgmma_rs256(float (&d)[128], uint32_t a0, uint32_t a1, uint32_t a2, uint32_t a3, uint32_t db, int sd) {
  asm volatile("{\n.reg .pred p;\n.reg .b64 da, db;\nmov.b64 db, {%132, %134};\nsetp.ne.b32 p, %133, 0;\n"
    "wgmma.mma_async.sync.aligned.m64n256k16.f32.bf16.bf16 {%0, %1, %2, %3, %4, %5, %6, %7, %8, %9, %10, %11, %12, %13, %14, %15, %16, %17, %18, %19, %20, %21, %22, %23, %24, %25, %26, %27, %28, %29, %30, %31, %32, %33, %34, %35, %36, %37, %38, %39, %40, %41, %42, %43, %44, %45, %46, %47, %48, %49, %50, %51, %52, %53, %54, %55, %56, %57, %58, %59, %60, %61, %62, %63, %64, %65, %66, %67, %68, %69, %70, %71, %72, %73, %74, %75, %76, %77, %78, %79, %80, %81, %82, %83, %84, %85, %86, %87, %88, %89, %90, %91, %92, %93, %94, %95, %96, %97, %98, %99, %100, %101, %102, %103, %104, %105, %106, %107, %108, %109, %110, %111, %112, %113, %114, %115, %116, %117, %118, %119, %120, %121, %122, %123, %124, %125, %126, %127}, {%128, %129, %130, %131}, db, p, 1, 1, 1;\n}\n"
    : "+f"(d[0]), "+f"(d[1]), "+f"(d[2]), "+f"(d[3]), "+f"(d[4]), "+f"(d[5]), "+f"(d[6]), "+f"(d[7]), "+f"(d[8]), "+f"(d[9]), "+f"(d[10]), "+f"(d[11]), "+f"(d[12]), "+f"(d[13]), "+f"(d[14]), "+f"(d[15]), "+f"(d[16]), "+f"(d[17]), "+f"(d[18]), "+f"(d[19]), "+f"(d[20]), "+f"(d[21]), "+f"(d[22]), "+f"(d[23]), "+f"(d[24]), "+f"(d[25]), "+f"(d[26]), "+f"(d[27]), "+f"(d[28]), "+f"(d[29]), "+f"(d[30]), "+f"(d[31]), "+f"(d[32]), "+f"(d[33]), "+f"(d[34]), "+f"(d[35]), "+f"(d[36]), "+f"(d[37]), "+f"(d[38]), "+f"(d[39]), "+f"(d[40]), "+f"(d[41]), "+f"(d[42]), "+f"(d[43]), "+f"(d[44]), "+f"(d[45]), "+f"(d[46]), "+f"(d[47]), "+f"(d[48]), "+f"(d[49]), "+f"(d[50]), "+f"(d[51]), "+f"(d[52]), "+f"(d[53]), "+f"(d[54]), "+f"(d[55]), "+f"(d[56]), "+f"(d[57]), "+f"(d[58]), "+f"(d[59]), "+f"(d[60]), "+f"(d[61]), "+f"(d[62]), "+f"(d[63]), "+f"(d[64]), "+f"(d[65]), "+f"(d[66]), "+f"(d[67]), "+f"(d[68]), "+f"(d[69]), "+f"(d[70]), "+f"(d[71]), "+f"(d[72]), "+f"(d[73]), "+f"(d[74]), "+f"(d[75]), "+f"(d[76]), "+f"(d[77]), "+f"(d[78]), "+f"(d[79]), "+f"(d[80]), "+f"(d[81]), "+f"(d[82]), "+f"(d[83]), "+f"(d[84]), "+f"(d[85]), "+f"(d[86]), "+f"(d[87]), "+f"(d[88]), "+f"(d[89]), "+f"(d[90]), "+f"(d[91]), "+f"(d[92]), "+f"(d[93]), "+f"(d[94]), "+f"(d[95]), "+f"(d[96]), "+f"(d[97]), "+f"(d[98]), "+f"(d[99]), "+f"(d[100]), "+f"(d[101]), "+f"(d[102]), "+f"(d[103]), "+f"(d[104]), "+f"(d[105]), "+f"(d[106]), "+f"(d[107]), "+f"(d[108]), "+f"(d[109]), "+f"(d[110]), "+f"(d[111]), "+f"(d[112]), "+f"(d[113]), "+f"(d[114]), "+f"(d[115]), "+f"(d[116]), "+f"(d[117]), "+f"(d[118]), "+f"(d[119]), "+f"(d[120]), "+f"(d[121]), "+f"(d[122]), "+f"(d[123]), "+f"(d[124]), "+f"(d[125]), "+f"(d[126]), "+f"(d[127])
    : "r"(a0), "r"(a1), "r"(a2), "r"(a3), "r"(db), "r"(sd), "r"(DESC_HI));
}

__device__ __forceinline__ void wgmma_ss256(float (&d)[128], uint32_t da, uint32_t db, int sd) {
  asm volatile("{\n.reg .pred p;\n.reg .b64 da, db;\nmov.b64 da, {%128, %131};\nmov.b64 db, {%129, %131};\nsetp.ne.b32 p, %130, 0;\n"
    "wgmma.mma_async.sync.aligned.m64n256k16.f32.bf16.bf16 {%0, %1, %2, %3, %4, %5, %6, %7, %8, %9, %10, %11, %12, %13, %14, %15, %16, %17, %18, %19, %20, %21, %22, %23, %24, %25, %26, %27, %28, %29, %30, %31, %32, %33, %34, %35, %36, %37, %38, %39, %40, %41, %42, %43, %44, %45, %46, %47, %48, %49, %50, %51, %52, %53, %54, %55, %56, %57, %58, %59, %60, %61, %62, %63, %64, %65, %66, %67, %68, %69, %70, %71, %72, %73, %74, %75, %76, %77, %78, %79, %80, %81, %82, %83, %84, %85, %86, %87, %88, %89, %90, %91, %92, %93, %94, %95, %96, %97, %98, %99, %100, %101, %102, %103, %104, %105, %106, %107, %108, %109, %110, %111, %112, %113, %114, %115, %116, %117, %118, %119, %120, %121, %122, %123, %124, %125, %126, %127}, da, db, p, 1, 1, 0, 1;\n}\n"
    : "+f"(d[0]), "+f"(d[1]), "+f"(d[2]), "+f"(d[3]), "+f"(d[4]), "+f"(d[5]), "+f"(d[6]), "+f"(d[7]), "+f"(d[8]), "+f"(d[9]), "+f"(d[10]), "+f"(d[11]), "+f"(d[12]), "+f"(d[13]), "+f"(d[14]), "+f"(d[15]), "+f"(d[16]), "+f"(d[17]), "+f"(d[18]), "+f"(d[19]), "+f"(d[20]), "+f"(d[21]), "+f"(d[22]), "+f"(d[23]), "+f"(d[24]), "+f"(d[25]), "+f"(d[26]), "+f"(d[27]), "+f"(d[28]), "+f"(d[29]), "+f"(d[30]), "+f"(d[31]), "+f"(d[32]), "+f"(d[33]), "+f"(d[34]), "+f"(d[35]), "+f"(d[36]), "+f"(d[37]), "+f"(d[38]), "+f"(d[39]), "+f"(d[40]), "+f"(d[41]), "+f"(d[42]), "+f"(d[43]), "+f"(d[44]), "+f"(d[45]), "+f"(d[46]), "+f"(d[47]), "+f"(d[48]), "+f"(d[49]), "+f"(d[50]), "+f"(d[51]), "+f"(d[52]), "+f"(d[53]), "+f"(d[54]), "+f"(d[55]), "+f"(d[56]), "+f"(d[57]), "+f"(d[58]), "+f"(d[59]), "+f"(d[60]), "+f"(d[61]), "+f"(d[62]), "+f"(d[63]), "+f"(d[64]), "+f"(d[65]), "+f"(d[66]), "+f"(d[67]), "+f"(d[68]), "+f"(d[69]), "+f"(d[70]), "+f"(d[71]), "+f"(d[72]), "+f"(d[73]), "+f"(d[74]), "+f"(d[75]), "+f"(d[76]), "+f"(d[77]), "+f"(d[78]), "+f"(d[79]), "+f"(d[80]), "+f"(d[81]), "+f"(d[82]), "+f"(d[83]), "+f"(d[84]), "+f"(d[85]), "+f"(d[86]), "+f"(d[87]), "+f"(d[88]), "+f"(d[89]), "+f"(d[90]), "+f"(d[91]), "+f"(d[92]), "+f"(d[93]), "+f"(d[94]), "+f"(d[95]), "+f"(d[96]), "+f"(d[97]), "+f"(d[98]), "+f"(d[99]), "+f"(d[100]), "+f"(d[101]), "+f"(d[102]), "+f"(d[103]), "+f"(d[104]), "+f"(d[105]), "+f"(d[106]), "+f"(d[107]), "+f"(d[108]), "+f"(d[109]), "+f"(d[110]), "+f"(d[111]), "+f"(d[112]), "+f"(d[113]), "+f"(d[114]), "+f"(d[115]), "+f"(d[116]), "+f"(d[117]), "+f"(d[118]), "+f"(d[119]), "+f"(d[120]), "+f"(d[121]), "+f"(d[122]), "+f"(d[123]), "+f"(d[124]), "+f"(d[125]), "+f"(d[126]), "+f"(d[127])
    : "r"(da), "r"(db), "r"(sd), "r"(DESC_HI));
}

__device__ __forceinline__ void wgmma_qkr(float (&d)[40], uint32_t a0, uint32_t a1, uint32_t a2, uint32_t a3, uint32_t db, int sd) {
  asm volatile("{\n.reg .pred p;\n.reg .b64 da, db;\nmov.b64 db, {%44, %46};\nsetp.ne.b32 p, %45, 0;\n"
    "wgmma.mma_async.sync.aligned.m64n80k16.f32.bf16.bf16 {%0, %1, %2, %3, %4, %5, %6, %7, %8, %9, %10, %11, %12, %13, %14, %15, %16, %17, %18, %19, %20, %21, %22, %23, %24, %25, %26, %27, %28, %29, %30, %31, %32, %33, %34, %35, %36, %37, %38, %39}, {%40, %41, %42, %43}, db, p, 1, 1, 0;\n}\n"
    : "+f"(d[0]), "+f"(d[1]), "+f"(d[2]), "+f"(d[3]), "+f"(d[4]), "+f"(d[5]), "+f"(d[6]), "+f"(d[7]), "+f"(d[8]), "+f"(d[9]), "+f"(d[10]), "+f"(d[11]), "+f"(d[12]), "+f"(d[13]), "+f"(d[14]), "+f"(d[15]), "+f"(d[16]), "+f"(d[17]), "+f"(d[18]), "+f"(d[19]), "+f"(d[20]), "+f"(d[21]), "+f"(d[22]), "+f"(d[23]), "+f"(d[24]), "+f"(d[25]), "+f"(d[26]), "+f"(d[27]), "+f"(d[28]), "+f"(d[29]), "+f"(d[30]), "+f"(d[31]), "+f"(d[32]), "+f"(d[33]), "+f"(d[34]), "+f"(d[35]), "+f"(d[36]), "+f"(d[37]), "+f"(d[38]), "+f"(d[39])
    : "r"(a0), "r"(a1), "r"(a2), "r"(a3), "r"(db), "r"(sd), "r"(DESC_HI));
}

__device__ __forceinline__ void wgmma_rs40(float (&d)[20], uint32_t a0, uint32_t a1, uint32_t a2, uint32_t a3, uint32_t db, int sd) {
  asm volatile("{\n.reg .pred p;\n.reg .b64 da, db;\nmov.b64 db, {%24, %26};\nsetp.ne.b32 p, %25, 0;\n"
    "wgmma.mma_async.sync.aligned.m64n40k16.f32.bf16.bf16 {%0, %1, %2, %3, %4, %5, %6, %7, %8, %9, %10, %11, %12, %13, %14, %15, %16, %17, %18, %19}, {%20, %21, %22, %23}, db, p, 1, 1, 0;\n}\n"
    : "+f"(d[0]), "+f"(d[1]), "+f"(d[2]), "+f"(d[3]), "+f"(d[4]), "+f"(d[5]), "+f"(d[6]), "+f"(d[7]), "+f"(d[8]), "+f"(d[9]), "+f"(d[10]), "+f"(d[11]), "+f"(d[12]), "+f"(d[13]), "+f"(d[14]), "+f"(d[15]), "+f"(d[16]), "+f"(d[17]), "+f"(d[18]), "+f"(d[19])
    : "r"(a0), "r"(a1), "r"(a2), "r"(a3), "r"(db), "r"(sd), "r"(DESC_HI));
}

__device__ __forceinline__ void wgmma_rs64t(float (&d)[32], uint32_t a0, uint32_t a1, uint32_t a2, uint32_t a3, uint32_t db, int sd) {
  asm volatile("{\n.reg .pred p;\n.reg .b64 da, db;\nmov.b64 db, {%36, %38};\nsetp.ne.b32 p, %37, 0;\n"
    "wgmma.mma_async.sync.aligned.m64n64k16.f32.bf16.bf16 {%0, %1, %2, %3, %4, %5, %6, %7, %8, %9, %10, %11, %12, %13, %14, %15, %16, %17, %18, %19, %20, %21, %22, %23, %24, %25, %26, %27, %28, %29, %30, %31}, {%32, %33, %34, %35}, db, p, 1, 1, 1;\n}\n"
    : "+f"(d[0]), "+f"(d[1]), "+f"(d[2]), "+f"(d[3]), "+f"(d[4]), "+f"(d[5]), "+f"(d[6]), "+f"(d[7]), "+f"(d[8]), "+f"(d[9]), "+f"(d[10]), "+f"(d[11]), "+f"(d[12]), "+f"(d[13]), "+f"(d[14]), "+f"(d[15]), "+f"(d[16]), "+f"(d[17]), "+f"(d[18]), "+f"(d[19]), "+f"(d[20]), "+f"(d[21]), "+f"(d[22]), "+f"(d[23]), "+f"(d[24]), "+f"(d[25]), "+f"(d[26]), "+f"(d[27]), "+f"(d[28]), "+f"(d[29]), "+f"(d[30]), "+f"(d[31])
    : "r"(a0), "r"(a1), "r"(a2), "r"(a3), "r"(db), "r"(sd), "r"(0x40000040u));
}

__device__ __forceinline__ uint32_t mkdesc(uint32_t addr, uint32_t lbo) { return ((addr & 0x3FFFF) >> 4) | ((lbo >> 4) << 16); }
#define WG_FENCE() asm volatile("wgmma.fence.sync.aligned;\n" ::: "memory")
#define WG_COMMIT() asm volatile("wgmma.commit_group.sync.aligned;\n" ::: "memory")
#define WG_WAIT(n) asm volatile("wgmma.wait_group.sync.aligned %0;\n" ::"n"(n) : "memory")
template <int N> __device__ __forceinline__ void pin(float (&d)[N]) {
#pragma unroll
  for (int i = 0; i < N; i++) asm volatile("" : "+f"(d[i])::"memory");
}
#define PROXY_FENCE() asm volatile("fence.proxy.async;\n" ::: "memory")
#define PROXY_FENCE_SMEM() asm volatile("fence.proxy.async.shared::cta;\n" ::: "memory")

__device__ __forceinline__ void mbar_init(uint32_t bar, uint32_t cnt) { asm volatile("mbarrier.init.shared::cta.b64 [%0], %1;\n" ::"r"(bar), "r"(cnt) : "memory"); }
__device__ __forceinline__ void mbar_expect_tx(uint32_t bar, uint32_t bytes) { asm volatile("mbarrier.arrive.expect_tx.shared::cta.b64 _, [%0], %1;\n" ::"r"(bar), "r"(bytes) : "memory"); }
__device__ __forceinline__ void mbar_arrive(uint32_t bar) { asm volatile("mbarrier.arrive.shared::cta.b64 _, [%0];\n" ::"r"(bar) : "memory"); }
__device__ __forceinline__ void mbar_wait(uint32_t bar, uint32_t parity) {
  asm volatile("{\n.reg .pred p;\n.reg .u32 n;\n.reg .u64 z;\nmov.u64 z, 0;\nmov.u32 n, 0;\n"
               "LAB_WAIT:\n"
               "mbarrier.try_wait.parity.shared::cta.b64 p, [%0], %1;\n"
               "@p bra LAB_DONE;\n"
               "add.u32 n, n, 1;\n"
               "setp.gt.u32 p, n, 100000000;\n"
               "@p st.global.u32 [z], n;\n"
               "bra LAB_WAIT;\n"
               "LAB_DONE:\n}\n" ::"r"(bar), "r"(parity) : "memory");
}
__device__ __forceinline__ void gwait(const unsigned* p, unsigned target) {
  asm volatile("{\n.reg .pred p;\n.reg .u32 n, v;\n.reg .u64 z;\nmov.u64 z, 0;\nmov.u32 n, 0;\n"
               "LAB_WAIT:\n"
               "ld.acquire.gpu.global.u32 v, [%0];\n"
               "sub.u32 v, v, %1;\n"
               "setp.ge.s32 p, v, 0;\n"
               "@p bra LAB_DONE;\n"
               "add.u32 n, n, 1;\n"
               "setp.gt.u32 p, n, 20000000;\n"
               "@p st.global.u32 [z], n;\n"
               "bra LAB_WAIT;\n"
               "LAB_DONE:\n}\n" ::"l"(p), "r"(target) : "memory");
}
#define GPU_FENCE() asm volatile("fence.acq_rel.gpu;\n" ::: "memory")
__device__ __forceinline__ void garrive(unsigned* p) { asm volatile("red.release.gpu.global.add.u32 [%0], 1;\n" ::"l"(p) : "memory"); }
__device__ __forceinline__ void garrive_relaxed(unsigned* p) { asm volatile("red.relaxed.gpu.global.add.u32 [%0], 1;\n" ::"l"(p) : "memory"); }
__device__ __forceinline__ void gset(unsigned* p, unsigned v) { asm volatile("st.release.gpu.global.u32 [%0], %1;\n" ::"l"(p), "r"(v) : "memory"); }
__device__ __forceinline__ void bulk_g2s(uint32_t dst, const void* src, uint32_t bytes, uint32_t bar) {
  asm volatile("cp.async.bulk.shared::cluster.global.mbarrier::complete_tx::bytes [%0], [%1], %2, [%3];\n" ::"r"(dst), "l"(src), "r"(bytes), "r"(bar) : "memory");
}
__device__ __forceinline__ void bar_sync(int id, int n) { asm volatile("bar.sync %0, %1;\n" ::"r"(id), "r"(n) : "memory"); }
__device__ __forceinline__ void bar_arrive(int id, int n) { asm volatile("bar.arrive %0, %1;\n" ::"r"(id), "r"(n) : "memory"); }
__device__ __forceinline__ float ex2(float x) { float y; asm("ex2.approx.ftz.f32 %0, %1;" : "=f"(y) : "f"(x)); return y; }
__device__ __forceinline__ float rcp(float x) { float y; asm volatile("rcp.approx.ftz.f32 %0, %1;" : "=f"(y) : "f"(x)); return y; }
__device__ __forceinline__ float rsq(float x) { float y; asm("rsqrt.approx.ftz.f32 %0, %1;" : "=f"(y) : "f"(x)); return y; }
__device__ __forceinline__ uint32_t pack2(float lo, float hi) { uint32_t r; asm("cvt.rn.bf16x2.f32 %0, %1, %2;" : "=r"(r) : "f"(hi), "f"(lo)); return r; }
__device__ __forceinline__ float blo(uint32_t v) { return __uint_as_float(v << 16); }
__device__ __forceinline__ float bhi(uint32_t v) { return __uint_as_float(v & 0xffff0000u); }
__device__ __forceinline__ uint4 ldg_nc(const void* p) { uint4 v; asm volatile("ld.global.nc.v4.u32 {%0,%1,%2,%3}, [%4];" : "=r"(v.x), "=r"(v.y), "=r"(v.z), "=r"(v.w) : "l"(p)); return v; }
__device__ __forceinline__ uint4 ldg_cg(const void* p) { uint4 v; asm volatile("ld.global.cg.v4.u32 {%0,%1,%2,%3}, [%4];" : "=r"(v.x), "=r"(v.y), "=r"(v.z), "=r"(v.w) : "l"(p) : "memory"); return v; }
__device__ __forceinline__ void stg128(void* p, uint32_t a, uint32_t b, uint32_t c, uint32_t d) { asm volatile("st.global.v4.u32 [%0], {%1,%2,%3,%4};" ::"l"(p), "r"(a), "r"(b), "r"(c), "r"(d) : "memory"); }
__device__ __forceinline__ void sts128(uint32_t p, uint32_t a, uint32_t b, uint32_t c, uint32_t d) { asm volatile("st.shared.v4.u32 [%0], {%1,%2,%3,%4};" ::"r"(p), "r"(a), "r"(b), "r"(c), "r"(d) : "memory"); }
__device__ __forceinline__ uint4 lds128(uint32_t p) { uint4 v; asm volatile("ld.shared.v4.u32 {%0,%1,%2,%3}, [%4];" : "=r"(v.x), "=r"(v.y), "=r"(v.z), "=r"(v.w) : "r"(p) : "memory"); return v; }
__device__ __forceinline__ float quad_sum(float v) { v += __shfl_xor_sync(~0u, v, 1); return v + __shfl_xor_sync(~0u, v, 2); }
__device__ __forceinline__ float quad_max(float v) { v = fmaxf(v, __shfl_xor_sync(~0u, v, 1)); return fmaxf(v, __shfl_xor_sync(~0u, v, 2)); }
__device__ __forceinline__ void mma16816(float (&d)[4], uint32_t a0, uint32_t a1, uint32_t a2, uint32_t a3, uint32_t b0, uint32_t b1) {
  asm("mma.sync.aligned.m16n8k16.row.col.f32.bf16.bf16.f32 {%0,%1,%2,%3}, {%4,%5,%6,%7}, {%8,%9}, {%0,%1,%2,%3};"
               : "+f"(d[0]), "+f"(d[1]), "+f"(d[2]), "+f"(d[3]) : "r"(a0), "r"(a1), "r"(a2), "r"(a3), "r"(b0), "r"(b1));
}
__device__ __forceinline__ uint32_t comp(const uint4& v, int i) { return i == 0 ? v.x : i == 1 ? v.y : i == 2 ? v.z : v.w; }
__device__ __forceinline__ void bulk_s2g(void* dst, uint32_t src, uint32_t bytes) {
  asm volatile("cp.async.bulk.global.shared::cta.bulk_group [%0], [%1], %2;\n" ::"l"(dst), "r"(src), "r"(bytes) : "memory");
}
__device__ __forceinline__ void bulk_red(void* dst, uint32_t src, uint32_t bytes) {
  asm volatile("cp.reduce.async.bulk.global.shared::cta.bulk_group.add.noftz.bf16 [%0], [%1], %2;\n" ::"l"(dst), "r"(src), "r"(bytes) : "memory");
}
#define BULK_COMMIT() asm volatile("cp.async.bulk.commit_group;\n" ::: "memory")
#define BULK_WAIT_READ() asm volatile("cp.async.bulk.wait_group.read 0;\n" ::: "memory")
#define BULK_WAIT() asm volatile("cp.async.bulk.wait_group 0;\n" ::: "memory")
__device__ __forceinline__ void prefetch_l2(const void* p, uint32_t bytes) { asm volatile("cp.async.bulk.prefetch.L2.global [%0], %1;" ::"l"(p), "r"(bytes)); }
__device__ __forceinline__ void cp16(uint32_t dst, const void* src) { asm volatile("cp.async.cg.shared.global [%0], [%1], 16;\n" ::"r"(dst), "l"(src) : "memory"); }
__device__ __forceinline__ void ldsm4(uint32_t (&r)[4], uint32_t p) {
  asm volatile("ldmatrix.sync.aligned.m8n8.x4.shared.b16 {%0,%1,%2,%3}, [%4];" : "=r"(r[0]), "=r"(r[1]), "=r"(r[2]), "=r"(r[3]) : "r"(p));
}
__device__ __forceinline__ void stsm4(uint32_t p, uint32_t a, uint32_t b, uint32_t c, uint32_t d) {
  asm volatile("stmatrix.sync.aligned.m8n8.x4.shared.b16 [%0], {%1,%2,%3,%4};" ::"r"(p), "r"(a), "r"(b), "r"(c), "r"(d) : "memory");
}
__device__ __forceinline__ uint32_t hfma2(uint32_t a, uint32_t b, uint32_t c) { uint32_t r; asm("fma.rn.bf16x2 %0, %1, %2, %3;" : "=r"(r) : "r"(a), "r"(b), "r"(c)); return r; }
__device__ __forceinline__ uint32_t hadd2(uint32_t a, uint32_t b) { uint32_t r; asm("add.rn.bf16x2 %0, %1, %2;" : "=r"(r) : "r"(a), "r"(b)); return r; }

__device__ __forceinline__ void product_load(const bool qk, const bool kperm, const __nv_bfloat16* __restrict__ L, const __nv_bfloat16* __restrict__ R,
                                             int d0, int c0, uint32_t sm) {
  const int ch = threadIdx.x & 31, w = threadIdx.x >> 5;
  const uint32_t smr = sm + 40 * 512;
  const __nv_bfloat16* lp = L + (d0 + (kperm ? ((w & 6) << 2) | (w & 1) : w)) * 256 + ch * 8;
  const uint32_t ls = sm + w * 512 + ((ch ^ w) << 4);
#pragma unroll
  for (int i = 0; i < 4; i++) cp16(ls + i * 4096, lp + i * (kperm ? 512 : 2048));
  cp16(ls + 4 * 4096, L + (248 + w) * 256 + ch * 8);
  if (qk) {
    const uint32_t rs = smr + (ch >> 3) * 1024 + w * 128 + (((ch ^ w) & 7) << 4);
#pragma unroll
    for (int i = 0; i < 4; i++) cp16(rs + i * 4096, R + (c0 + w + i * 8) * 256 + ch * 8);
    cp16(rs + 4 * 4096, R + (248 + w) * 256 + ch * 8);
  } else {
    const int e = w * 4 + (ch >> 3);
#pragma unroll
    for (int i = 0; i < 8; i++) cp16(smr + (e + i * 32) * 128 + (((ch ^ e) & 7) << 4), R + (e + i * 32) * 256 + c0 + (ch & 7) * 8);
  }
}
template <bool qk>
__device__ __forceinline__ void product_mma(uint8_t* img, int d0, int c0, uint32_t sm) {
  const int lane = threadIdx.x & 31, w = (threadIdx.x >> 5) & 3, l7 = lane & 7;
  const uint32_t pa = sm + (((lane & 8) ? 32 : w * 8) + l7) * 512;
  const uint32_t bd = mkdesc(sm + 40 * 512, 16);
  uint32_t a[16][4];
#pragma unroll
  for (int u = 0; u < 16; u++) ldsm4(a[u], pa + (u >> 2) * 128 + ((((u & 3) * 2 + (lane >> 4)) ^ l7) << 4));
  constexpr int NT = qk ? 4 : 8;
  float m[qk ? 20 : 32];
  pin(m);
  WG_FENCE();
#pragma unroll
  for (int u = 0; u < 16; u++) {
    if constexpr (qk) wgmma_rs40(m, a[u][0], a[u][1], a[u][2], a[u][3], bd + (u >> 2) * 64 + (u & 3) * 2, u);
    else wgmma_rs64t(m, a[u][0], a[u][1], a[u][2], a[u][3], bd + u * 128, u);
  }
  WG_COMMIT();
  WG_WAIT(0);
  pin(m);
  STAMPIF(threadIdx.x == 256, 27);
  float z = 0.f, u = 0.f;
  if constexpr (qk) { z = quad_sum(m[18] + m[19]); u = quad_sum(m[16] + m[17]); }
#pragma unroll
  for (int o = 4; o < 32; o *= 2) {
#pragma unroll
    for (int n = 0; n < NT; n++) { m[4 * n + 2] += __shfl_xor_sync(~0u, m[4 * n + 2], o); m[4 * n + 3] += __shfl_xor_sync(~0u, m[4 * n + 3], o); }
    if constexpr (qk) z += __shfl_xor_sync(~0u, z, o);
  }
  const int g = lane >> 2, t = lane & 3;
  u -= z * 0.125f;
  const float sc = d0 + w * 8 + g == 255 ? 0.f : qk ? 1.4426950408889634f / 16.f : 1.f;
  uint32_t v[NT];
#pragma unroll
  for (int n = 0; n < NT; n++) v[n] = pack2(fmaf(m[4 * n + 2] + u, -0.125f, m[4 * n]) * sc, fmaf(m[4 * n + 3] + u, -0.125f, m[4 * n + 1]) * sc);
  uint8_t* gp = img + ((d0 >> 3) + w) * 4096 + (c0 >> 6) * 1024 + g * 128;
  if constexpr (qk) {
    if (c0 == 224 && t == 3) v[3] &= 0xffffu;
    const uint32_t so = sm + 57344 + w * 1024;
    stsm4(so + l7 * 128 + (((lane >> 3) ^ l7) << 4), v[0], v[1], v[2], v[3]);
    __syncwarp();
    const uint4 r = lds128(so + g * 128 + ((t ^ g) << 4));
    stg128(gp + (((t + ((c0 >> 3) & 4)) ^ g) << 4), r.x, r.y, r.z, r.w);
  } else {
    stg128(gp + ((t ^ g) << 4), v[0], v[1], v[2], v[3]);
    stg128(gp + (((t + 4) ^ g) << 4), v[4], v[5], v[6], v[7]);
  }
}
__device__ __forceinline__ void product_done(unsigned* ctr) {
  STAMPIF(threadIdx.x == 256, 31);
  bar_sync(5, 128);
  if (threadIdx.x == (blockIdx.x < 64 ? 256 : 288)) garrive(ctr);
  STAMPIF(threadIdx.x == 288, 34);
  __syncwarp();
  if (blockIdx.x < 64) bar_arrive(7, 256);
}

__global__ void __launch_bounds__(384, 1)
gps_kernel(const __nv_bfloat16* __restrict__ x, const int* __restrict__ src, const int* __restrict__ dst,
           const __nv_bfloat16* __restrict__ deg_inv, const __nv_bfloat16* __restrict__ w_msg,
           const __nv_bfloat16* __restrict__ wq, const __nv_bfloat16* __restrict__ wk, const __nv_bfloat16* __restrict__ wv,
           const __nv_bfloat16* __restrict__ w_out, __nv_bfloat16* __restrict__ out, Scratch* G) {
  extern __shared__ __align__(1024) uint8_t smem_raw[];
  const uint32_t sb = (uint32_t)__cvta_generic_to_shared(smem_raw);
  const uint32_t ring = sb + SM_RING, full0 = sb + SM_BAR, empty0 = full0 + 8 * NST, qbar0 = empty0 + 8 * NST;
  const uint32_t evt0 = qbar0 + 16, one0 = evt0 + 112;
  const uint32_t sfree = one0, wsent = one0 + 8, wfirst = one0 + 16, go = one0 + 24, bbar = one0 + 32, hread0 = one0 + 40, xbar0 = one0 + 56, cbar = one0 + 120, ebar = one0 + 128;
  const int wg = __shfl_sync(~0u, threadIdx.x >> 7, 0);
  const int lane = threadIdx.x & 31;
  const int cta = blockIdx.x;
  GSTAMPIF(threadIdx.x == 0, 0);
  const bool prod = cta < 126 || cta >= 130;
  const int pi = cta < 126 ? cta : cta - 4;
  const int kind = max((pi >> 5) - 1, 0), pd0 = ((pi >> (kind ? 2 : 3)) & 7) * 32, pc0 = kind ? (pi & 3) * 64 : (pi & 7) * 32;
  const bool early = cta > 125 && cta < 131;
  const int xfirst = cta == 130 ? 1 : early ? 4 : 0;
  const uint32_t cnt = sb + SM_META, box = sb + SM_AUX;
  const int e0 = cta * 1216, ne = min(E_ - e0, 1216);
  if (wg < 2) {
    if (prod) product_load(kind == 0, kind == 1, kind == 0 ? wq : kind == 1 ? w_msg : wv, kind == 0 ? wk : w_out, pd0, pc0, ring);
  } else if (threadIdx.x < 320) {
#pragma unroll 1
    for (int i = threadIdx.x - 256; i < 1024 + 32; i += 64) sts128(i < 1024 ? box + i * 16 : cnt + (i - 1024) * 16, 0, 0, 0, 0);
  } else if (threadIdx.x == 352) {
    cp16(sb + SM_BAR + 496, &G->epoch);
  } else if (threadIdx.x == 320) {
#pragma unroll
    for (int i = 0; i < 39; i++) mbar_init(full0 + 8 * i, i >= 3 && i < 6 ? 8 : i >= 8 && i < 22 ? 128 : i == 37 ? 384 : 1);
    asm volatile("fence.mbarrier_init.release.cluster;\n" ::: "memory");
    const int r = cta % 5, t0 = (cta / 5) * 3 + (r < 3 ? r : r - 2);
#pragma unroll 1
    for (int i = 0; i < xfirst; i++) {
      const int pc = r < 3 ? i : i ^ 4;
      mbar_expect_tx(xbar0 + 8 * i, 8192);
      bulk_g2s(sb + SM_Q + pc * 8192, x + (size_t)(t0 * 128 + pc * 16) * 256, 8192, xbar0 + 8 * i);
    }
  }
  STAMPIF(threadIdx.x == 128, 26);

  const int grp = cta / 5, role = cta < 130 ? cta - grp * 5 : (cta == 130 ? 1 : 5);
  const bool owner = role < 3;
  const int tA = grp * 3;
  int q0, n0, o0, q1 = 0, k1 = 0, n1 = 0, i1 = -1;
  if (cta >= 130) { q0 = 78; n0 = owner ? 64 : NKV - 64; o0 = 78; if (owner) i1 = 78; }
  else if (owner) { q0 = tA + role; n0 = role == 0 ? SCHED_A : role == 1 ? SCHED_B : SCHED_C; i1 = o0 = q0; }
  else if (role == 3) { q0 = tA + 1; n0 = SCHED_B1; o0 = NQT + grp; q1 = tA; k1 = SCHED_A; n1 = NKV - SCHED_A; }
  else { q0 = tA + 2; n0 = NKV - SCHED_C; o0 = q0; q1 = tA + 1; k1 = SCHED_B; n1 = NKV - SCHED_B - SCHED_B1; i1 = NQT + grp; }
  const int lu = (role == 3 ? tA : q0) * 2, lu2 = (tA + 1) * 2 + role - 3;

  const bool staged = role == 3;

  __syncthreads();
  asm volatile("cp.async.mbarrier.arrive.noinc.shared::cta.b64 [%0];\n" ::"r"(cbar) : "memory");

  if (wg == 2) {
    STAMPIF(threadIdx.x == 256, 40);
    mbar_wait(cbar, 0);
    if (prod) {
      PROXY_FENCE_SMEM();
      STAMPIF(threadIdx.x == 256, 24);
      if (kind == 0) product_mma<true>(G->w, pd0, pc0, ring); else product_mma<false>(G->w + kind * 131072, pd0, pc0, ring);
      product_done(&G->ctr[kind ? C_M : C_W]);
    }
    asm volatile("setmaxnreg.dec.sync.aligned.u32 56;\n");
    unsigned ep;
    asm volatile("ld.shared.u32 %0, [%1];" : "=r"(ep) : "r"(sb + SM_BAR + 496) : "memory");
    ep += 1;
    const int w = (threadIdx.x >> 5) & 3;
    if (w == 0) {
      if (lane == 0) {
        STAMPIF(true, 1);
        uint32_t st = 0, ph = 1;
        auto push = [&](const uint8_t* p, const uint8_t* rem) {
          mbar_wait(empty0 + 8 * st, ph);
          mbar_expect_tx(full0 + 8 * st, rem ? STB + 8192 : STB);
          bulk_g2s(ring + st * STB, p, STB, full0 + 8 * st);
          if (rem) bulk_g2s(sb + SM_REM, rem, 8192, full0 + 8 * st);
          if (++st == NST) { st = 0; ph ^= 1; }
        };
        auto qfill = [&](int e, int h, const uint8_t* p, const unsigned* flag, unsigned target, const float2* meta) {
          if (flag) gwait(flag, target);
          mbar_wait(evt0 + 16 * e + 8 * h, 0);
          PROXY_FENCE_SMEM();
          mbar_expect_tx(qbar0 + 8 * h, meta ? 32768 + 512 : 32768);
          bulk_g2s(sb + SM_Q + h * 32768, p + h * 32768, 32768, qbar0 + 8 * h);
          if (meta) bulk_g2s(sb + SM_META + h * 512, meta, 512, qbar0 + 8 * h);
        };
        auto lload = [&](int u, int blk, uint32_t dst) {
          const uint32_t lfull = xbar0 + 8 * u;
          const uint32_t nd = blk < 156 ? 128 : blk == 156 ? 32 : 0;
          mbar_expect_tx(lfull, 32768 + nd);
          bulk_g2s(dst, G->acc + (size_t)blk * 32768, 32768, lfull);
          if (nd) bulk_g2s(sb + SM_DINV + u * 128, deg_inv + blk * 64, nd, lfull);
        };
        gwait(&G->ctr[C_W], ep * CNT_W);
        PROXY_FENCE_SMEM();
        STAMPIF(true, 2);
        mbar_expect_tx(wfirst, 16384);
        bulk_g2s(ring, G->w, 16384, wfirst);
        mbar_expect_tx(full0, STB - 16384);
        bulk_g2s(ring + 16384, G->w + 16384, STB - 16384, full0);
        st = 1;
#pragma unroll 1
        for (int i = 1; i < 3; i++) push(G->w + i * STB, i == 2 ? G->w + 3 * STB : nullptr);
        mbar_arrive(wsent);
        gwait(&G->ctr[C_E], ep * CNT_E);
        STAMPIF(true, 3);
        const int ntot = n0 + n1;
        int h1 = 1;
#pragma unroll 1
        for (int j = 0; j < ntot + 3; j++) {
          if (j == (owner ? 2 : 1)) gwait(&G->ctr[C_F], ep * CNT_F);
          if (j == 3) gwait(&G->ctr[C_H], ep * CNT_H);
          if (j == ntot) {
            gwait(&G->ctr[C_G], ep * CNT_G);
            PROXY_FENCE_SMEM();
            if (role == 4) lload(0, lu, sb + SM_AUX);
            if (role == 3) lload(2, lu2, sb + SM_AUX);
          }
          int kt = j >= n0 ? k1 + j - n0 : owner ? j : NKV - 1 - j;
          if (kt < 3) kt = kt == 2 ? 117 : 123 - kt; else if (kt >= 117 && kt < 120) kt -= 117; else if (kt == 122 || kt == 123) kt -= 4;
          const uint8_t* wp_ = G->w + (owner ? 262144 : 131072) + (j - ntot) * STB;
          push(j < ntot ? G->ht + (size_t)kt * STB : wp_, j == ntot ? wp_ + 3 * STB : nullptr);
          if (j == JBG) { mbar_arrive(qbar0); mbar_arrive(qbar0 + 8); }
          if (j == JSCAT) mbar_arrive(go);
          if (n1) {
            const int h = j - n0;
            if (h == 0 || h == 1) qfill(1, h, G->qt + (size_t)q1 * 65536, h ? nullptr : &G->ctr[C_M], ep * CNT_M, nullptr);
          }
          const int h = j - ntot;
          if (h == 1 && owner) {
            unsigned v, fr;
            do {
              asm volatile("{\n.reg .pred p;\nmbarrier.test_wait.parity.shared::cta.b64 p, [%1], %2;\nselp.u32 %0, 1, 0, p;\n}\n" : "=r"(fr) : "r"(empty0 + 8 * st), "r"(ph) : "memory");
              asm volatile("ld.acquire.gpu.global.u32 %0, [%1];" : "=r"(v) : "l"(&G->pflag[i1 * 2 + 1]) : "memory");
            } while (v != ep && !fr);
            if (v != ep) h1 = 2;
          }
          if ((h == 0 || h == h1) && i1 >= 0)
            qfill(n1 ? 6 : 1, h != 0, G->part + (size_t)i1 * 65536, h == 1 && owner ? nullptr : &G->pflag[i1 * 2 + (h != 0)], ep, &G->meta[i1 * 128 + (h != 0) * 64]);
          if ((h == 0 || h == 1) && i1 < 0) { mbar_wait(evt0 + (n1 ? 96 : 16) + 8 * h, 0); lload(h, lu + h, sb + SM_Q + h * 32768); }
        }
        if (role == 4) {
          mbar_wait(evt0 + 80, 0); PROXY_FENCE_SMEM(); mbar_wait(wsent, 1); lload(1, lu + 1, sb + SM_AUX);
          mbar_wait(evt0 + 88, 0); PROXY_FENCE_SMEM(); mbar_wait(wfirst, 1); lload(2, lu2, sb + SM_AUX);
        }
        if (cta == 0) G->epoch = ep;
      }
    } else {
      if (w == 3 && lane == 0) {
        const int pub = role == 0 ? 3 : owner ? 1 : 2;
        if (!early) mbar_wait(wsent, 0);
#pragma unroll 1
        for (int h = 0; h < 2; h++) {
          if (pub >> h & 1) { mbar_wait(evt0 + 64 + 8 * h, 0); bulk_s2g(G->ht + (size_t)q0 * 65536 + h * 32768, sb + SM_Q + h * 32768, cta < 130 ? 32768 : 8192); }
          BULK_COMMIT();
        }
        asm volatile("cp.async.bulk.wait_group 1;\n" ::: "memory");
        mbar_arrive(hread0);
        BULK_WAIT();
        mbar_arrive(hread0 + 8);
        GPU_FENCE();
        if (early) garrive_relaxed(&G->ctr[C_E]);
        if (cta > 120 && cta < 125) garrive_relaxed(&G->ctr[C_F]);
        garrive_relaxed(&G->ctr[C_H]);
        STAMPIF(true, 30);
      }
      __syncwarp();
      mbar_wait(qbar0 + 8, 0);
      if (w < 3) {
        const uint32_t eb = box + 16384;
        if (threadIdx.x == 288) {
          mbar_expect_tx(ebar, ne * 8);
          bulk_g2s(eb, src + e0, ne * 4, ebar);
          bulk_g2s(eb + 8192, dst + e0, ne * 4, ebar);
        }
        __syncwarp();
        mbar_wait(ebar, 0);
#pragma unroll 1
        for (int i = threadIdx.x - 288; i < ne / 4; i += 64) {
          const uint4 vs = lds128(eb + i * 16), vd = lds128(eb + 8192 + i * 16);
          uint32_t tl[4], sl[4];
#pragma unroll
          for (int u = 0; u < 4; u++) {
            tl[u] = comp(vs, u) / BN;
            asm volatile("atom.shared.add.u32 %0, [%1], 1;" : "=r"(sl[u]) : "r"(cnt + tl[u] * 4) : "memory");
          }
#pragma unroll
          for (int u = 0; u < 4; u++)
            if (sl[u] < 32) asm volatile("st.shared.u32 [%0], %1;" ::"r"(box + tl[u] * 128 + sl[u] * 4), "r"(0x80000000u | (comp(vs, u) - tl[u] * BN) << 14 | comp(vd, u)) : "memory");
          if ((sl[0] | sl[1] | sl[2] | sl[3]) >= 32) {
#pragma unroll 1
            for (int u = 0; u < 4; u++) {
              const uint32_t a = u & 1 ? (u & 2 ? sl[3] : sl[1]) : (u & 2 ? sl[2] : sl[0]);
              if (a >= 32) {
                uint32_t k;
                asm volatile("atom.shared.add.u32 %0, [%1], 1;" : "=r"(k) : "r"(cnt + NKV * 4) : "memory");
                G->ovf[cta * 1280 + k] = comp(vs, u) << 14 | comp(vd, u);
              }
            }
          }
        }
        PROXY_FENCE_SMEM();
        STAMPIF(threadIdx.x == 288, 36);
        bar_arrive(8, 96);
      }
      if (w == 3) {
#pragma unroll 4
        for (int i = 0; i < 16; i++) sts128(sb + SM_REM + i * 512 + lane * 16, 0, 0, 0, 0);
        PROXY_FENCE_SMEM();
        bar_sync(8, 96);
        if (lane == 0) {
#pragma unroll 1
          for (int i = 0; i < 5; i++) {
            const size_t off = (size_t)cta * 40960 + i * 8192;
            if (cta < NKV) { mbar_expect_tx(bbar, 8192); bulk_g2s(box + 16384, (const uint8_t*)x + off, 8192, bbar); }
            bulk_s2g(G->acc + off, sb + SM_REM, 8192);
            if (cta < NKV) { mbar_wait(bbar, i & 1); bulk_s2g((uint8_t*)out + off, box + 16384, 8192); }
            BULK_COMMIT();
            BULK_WAIT();
          }
          if (cta < 130 && role < 2) {
            mbar_wait(evt0, 0);
            mbar_wait(evt0 + 8, 0);
#pragma unroll 1
            for (int i = 0; i < 8; i++) {
              bulk_s2g(G->qt + (size_t)q0 * 65536 + i * 8192, sb + SM_Q + i * 8192, 8192);
              BULK_COMMIT();
              BULK_WAIT();
            }
          }
        }
        __syncwarp();
        bar_arrive(6, 96);
        if (lane == 0 && !owner) {
#pragma unroll 1
          for (int u = n1 ? 0 : 2; u < 4; u++) {
            mbar_wait(evt0 + 32 + 8 * u, 0);
            if (staged && u == 0) {
              mbar_wait(evt0 + 40, 0);
#pragma unroll 1
              for (int i = 0; i < 10; i++) {
                bulk_s2g(G->part + (size_t)o0 * 65536 + (i < 5 ? i * 4096 : 12288 + i * 4096), sb + SM_REM + i * 4096, 4096);
                BULK_COMMIT();
                BULK_WAIT();
              }
              mbar_arrive(sfree);
            }
            gset(&G->pflag[(u < 2 || !n1 ? o0 : q1) * 2 + (u & 1)], ep);
            if (u >= 2) mbar_arrive(u == 2 ? wsent : wfirst);
          }
        }
      } else {
        bar_sync(6, 96);
        int novf;
        asm volatile("ld.shared.u32 %0, [%1];" : "=r"(novf) : "r"(cnt + NKV * 4) : "memory");
        if (threadIdx.x == 288) {
          bulk_s2g(G->box + cta * NKV * 32, box, NKV * 128);
          BULK_COMMIT();
          BULK_WAIT();
          garrive(&G->ctr[C_M]);
          STAMPIF(true, 43);
          gwait(&G->ctr[C_H], ep * CNT_H);
          if (staged) mbar_wait(sfree, 0);
          if (cta < NKV) { mbar_expect_tx(bbar, STB); bulk_g2s(sb + SM_REM, G->ht + (size_t)cta * STB, STB, bbar); }
        }
        __syncwarp();
        if (cta < NKV) {
          mbar_wait(bbar, 1);
#pragma unroll 1
          for (int gi = 0; gi < 10; gi++) {
            uint4 v[4];
#pragma unroll
            for (int u = 0; u < 4; u++) { const int rr = (w - 1) * 4 + u; v[u] = lds128(sb + SM_REM + gi * 4096 + (lane >> 3) * 1024 + rr * 128 + (((lane ^ rr) & 7) << 4)); }
            bar_sync(5, 64);
#pragma unroll
            for (int u = 0; u < 4; u++) sts128(sb + SM_REM + gi * 4096 + ((w - 1) * 4 + u) * 512 + lane * 16, v[u].x, v[u].y, v[u].z, v[u].w);
          }
          PROXY_FENCE_SMEM();
          bar_sync(5, 64);
        }
        STAMPIF(threadIdx.x == 288, 44);
        mbar_wait(go, 0);
        if (lane == 0) gwait(&G->ctr[C_M], ep * CNT_M);
        __syncwarp();
        STAMPIF(threadIdx.x == 288, 4);
        if (cta < NKV) {
          const unsigned* bp = G->box + ((w - 1) * NKV + cta) * 32 + lane;
          unsigned e = __ldcg(bp);
#pragma unroll 1
          for (int i = 0; i < NCTA / 2; i++) {
            bp += 2 * NKV * 32;
            unsigned en = 0;
            if (i + 1 < NCTA / 2) en = __ldcg(bp);
            if (e) bulk_red(G->acc + (size_t)(e & 0x3fff) * 512, sb + SM_REM + ((e >> 14) & 127) * 512, 512);
            BULK_COMMIT();
            BULK_WAIT_READ();
            e = en;
          }
        }
#pragma unroll 1
        for (int i = w - 1; i < novf; i += 2) {
          const int e = __ldcg(&G->ovf[cta * 1280 + i]), r = e >> 14;
          const uint4 v = ldg_cg(G->ht + (size_t)(r >> 3) * 4096 + (lane >> 3) * 1024 + (r & 7) * 128 + (((lane ^ r) & 7) << 4));
          asm volatile("red.global.add.noftz.v4.bf16x2 [%0], {%1,%2,%3,%4};" ::"l"(G->acc + (size_t)(e & 0x3fff) * 512 + lane * 16), "r"(v.x), "r"(v.y), "r"(v.z), "r"(v.w) : "memory");
        }
        BULK_WAIT();
        __syncwarp();
        if (lane == 0) garrive(&G->ctr[C_G]);
        STAMPIF(threadIdx.x == 288, 5);
      }
    }
  } else {
    const int g = lane >> 2, t = lane & 3, wp = __shfl_sync(~0u, (threadIdx.x >> 5) & 3, 0), tid = threadIdx.x & 127;
    const uint32_t qh = sb + SM_Q + wg * 32768;
    const uint32_t qw = qh + wp * 8192;
    const uint32_t qbar = qbar0 + 8 * wg;
    auto event = [&](int e) { mbar_arrive(evt0 + 16 * e + 8 * wg); };
    if (wg == 1) bar_arrive(1, 256);
    {
      const int xr0 = min(q0 * 128 + wg * 64 + wp * 16, N_ - 16), xord = (owner || !early ? wg : wg ^ 1) * 4 + wp;
      auto xload = [&]() {
        if (lane == 0 && xord >= xfirst) {
          mbar_expect_tx(xbar0 + 8 * xord, 8192);
          bulk_g2s(qw, x + (size_t)xr0 * 256, 8192, xbar0 + 8 * xord);
        }
      };
      if (xord < 4) xload();
      if (xord >= 4) {
        mbar_wait(xbar0 + 8 * (xord - 4), 0);
        if (cta < 64) {
          if (lane == 0) prefetch_l2(x + (size_t)xr0 * 256, 8192);
          bar_sync(7, 256);
        }
        xload();
      }
      STAMPIF(threadIdx.x == 0, 35);
      mbar_wait(xbar0 + 8 * xord, 0);
      STAMPIF(threadIdx.x == 0, 25);
      STAMPIF(threadIdx.x == 224, 41);
      uint4 xa[8], xb[8];
      const uint32_t sw = (g & 1) << 6;
#pragma unroll
      for (int J = 0; J < 8; J++) xa[J] = lds128(qw + g * 512 + t * 16 + ((J * 64) ^ sw));
#pragma unroll
      for (int J = 0; J < 8; J++) xb[J] = lds128(qw + 4096 + g * 512 + t * 16 + ((J * 64) ^ sw));
      __syncwarp();
      const uint32_t wa = qw + g * 128 + (((t ^ g) << 4) ^ sw);
#pragma unroll
      for (int rr = 0; rr < 2; rr++) {
        float sm[2][4] = {}, f[64], q[4] = {};
#pragma unroll
        for (int J = 0; J < 8; J++) {
          const uint4 v = rr ? xb[J] : xa[J];
          mma16816(sm[J & 1], v.x, v.y, v.z, v.w, 0x3f803f80u, 0x3f803f80u);
#pragma unroll
          for (int i = 0; i < 4; i++) {
            f[J * 8 + 2 * i] = blo(comp(v, i)); f[J * 8 + 2 * i + 1] = bhi(comp(v, i));
            q[i] = fmaf(f[J * 8 + 2 * i], f[J * 8 + 2 * i], q[i]); q[i ^ 2] = fmaf(f[J * 8 + 2 * i + 1], f[J * 8 + 2 * i + 1], q[i ^ 2]);
          }
        }
        const float mean = ((sm[0][0] + sm[0][2]) + (sm[1][0] + sm[1][2])) * (1.f / 256.f);
        const float rstd = rsq(fmaxf(fmaf(-mean, mean, quad_sum((q[0] + q[1]) + (q[2] + q[3])) * (1.f / 256.f)), 0.f) + 1e-5f);
#pragma unroll
        for (int J = 0; J < 8; J++) {
          const bool lastc = J >= 6 && (lane & 7) == (J == 7 ? 3 : 7);
          const float c = (lastc ? f[J * 8 + 7] : mean) * -rstd;
          uint32_t r3 = pack2(fmaf(f[J * 8 + 6], rstd, c), fmaf(f[J * 8 + 7], rstd, c));
          if (lastc) r3 = (r3 & 0xffffu) | 0x3f800000u;
          sts128((wa ^ ((J & 1) << 6)) + rr * 4096 + (J >> 1) * 1024, pack2(fmaf(f[J * 8], rstd, c), fmaf(f[J * 8 + 1], rstd, c)),
                 pack2(fmaf(f[J * 8 + 2], rstd, c), fmaf(f[J * 8 + 3], rstd, c)), pack2(fmaf(f[J * 8 + 4], rstd, c), fmaf(f[J * 8 + 5], rstd, c)), r3);
        }
      }
      STAMPIF(threadIdx.x == 0, 38);
      PROXY_FENCE_SMEM();
      STAMPIF(threadIdx.x == 0, 39);
    }
    event(4);
    bar_sync(3 + wg, 128);
    STAMPIF(tid == 0, wg ? 42 : 6);
    asm volatile("setmaxnreg.inc.sync.aligned.u32 224;\n");

    float o[128];
    uint32_t ga[64], qr[NQR * 4];
    uint32_t st = 0, ph = 0, pst = 0;
    const uint32_t qd = mkdesc(qh, 16), kd0 = mkdesc(ring, 16), vd0 = mkdesc(ring, 1024), rd = mkdesc(sb + SM_REM, 1024);
    auto wait_full = [&]() { mbar_wait(full0 + 8 * st, ph); };
    auto advance = [&]() { pst = st; if (++st == NST) { st = 0; ph ^= 1; } };
    auto release = [&]() { if (lane == 0) mbar_arrive(empty0 + 8 * pst); };

    {
      mbar_wait(wfirst, 0);
      bar_sync(1 + wg, 256);
      STAMPIF(threadIdx.x == 0, 28);
      WG_FENCE();
      wgmma_ss256(o, qd, vd0, 0);
      wgmma_ss256(o, qd + 2, vd0 + 512, 1);
#pragma unroll
      for (int c = 0; c < 3; c++) {
        wait_full();
        WG_FENCE();
#pragma unroll
        for (int k = c ? 0 : 2; k < 5; k++) { const int ks = c * 5 + k; wgmma_ss256(o, qd + (ks >> 2) * 64 + (ks & 3) * 2, vd0 + c * (STB >> 4) + k * 512, ks != 0); }
        if (c == 2) wgmma_ss256(o, qd + 3 * 64 + 6, rd, 1);
        WG_COMMIT();
        if (c == 2) bar_arrive(2 - wg, 256);
        if (c > 0) { WG_WAIT(1); release(); }
        advance();
      }
      WG_WAIT(0);
      pin(o);
      release();
      STAMPIF(threadIdx.x == 0, 29);
      mbar_wait(hread0 + 8 * wg, 0);
      bar_sync(3 + wg, 128);
      STAMPIF(threadIdx.x == 0, 45);
      const uint32_t sa = qw + ((lane >> 3) & 1) * 4096 + (lane & 7) * 128 + (((lane >> 4) ^ (lane & 7)) << 4);
#pragma unroll
      for (int i = 0; i < 32; i += 2)
        stsm4((sa ^ ((i & 7) << 4)) + (i >> 3) * 1024, pack2(o[4 * i], o[4 * i + 1]), pack2(o[4 * i + 2], o[4 * i + 3]), pack2(o[4 * i + 4], o[4 * i + 5]), pack2(o[4 * i + 6], o[4 * i + 7]));
#pragma unroll
      for (int i = 0; i < NQR * 4; i++) qr[i] = pack2(o[128 - NQR * 8 + 2 * i], o[129 - NQR * 8 + 2 * i]);
      STAMPIF(threadIdx.x == 0, 46);
      PROXY_FENCE_SMEM();
      event(0);
    }
    STAMPIF(threadIdx.x == 0, 7);

    float s[BN / 2];
    uint32_t p[BN / 4];
    float m0, m1, mb0, mb1, l0, l1;
    auto qk = [&]() {
#pragma unroll
      for (int ks = 0; ks < 16; ks++) {
        const uint32_t off = (ks >> 2) * 64 + (ks & 3) * 2;
        const int r = (ks - 16 + NQR) * 4;
        const uint64_t q64 = (uint64_t)DESC_HI << 32 | qd, k64 = ((uint64_t)DESC_HI << 32 | kd0) + st * (STB >> 4);
        if (r < 0) wgmma_qk64(s, q64 + off, k64 + off, ks > 0);
        else wgmma_qkr64(s, qr[r], qr[r + 1], qr[r + 2], qr[r + 3], k64 + off, 1);
      }
      WG_COMMIT();
    };
    auto pv = [&](int keep) {
#pragma unroll
      for (int ks = 0; ks < BN / 16; ks++) wgmma_pv64(o, p[ks * 4], p[ks * 4 + 1], p[ks * 4 + 2], p[ks * 4 + 3], ((uint64_t)DESC_HI << 32 | vd0) + pst * (STB >> 4) + ks * 512, ks ? 1 : keep);
      WG_COMMIT();
    };
    auto softmax_slow = [&](bool dump, bool first) {
      const float om0 = m0, om1 = m1;
      if (dump) {
        m0 = m1 = -INFINITY;
        mb0 = mb1 = 0.f;
        if (staged) {
#pragma unroll
          for (int k = 0; k < 10; k++)
            sts128(sb + SM_REM + wg * 20480 + k * 2048 + tid * 16, pack2(o[8 * k], o[8 * k + 1]), pack2(o[8 * k + 2], o[8 * k + 3]), pack2(o[8 * k + 4], o[8 * k + 5]), pack2(o[8 * k + 6], o[8 * k + 7]));
          PROXY_FENCE_SMEM();
        }
      }
      float x0 = fmaxf(s[0], s[1]), x1 = fmaxf(s[2], s[3]);
#pragma unroll
      for (int i = 1; i < BN / 8; i++) { x0 = fmaxf(x0, fmaxf(s[4 * i], s[4 * i + 1])); x1 = fmaxf(x1, fmaxf(s[4 * i + 2], s[4 * i + 3])); }
      x0 = quad_max(x0) + mb0; x1 = quad_max(x1) + mb1;
      float r0 = x0 < m0 ? m0 : ceilf(x0 + 32.f), r1 = x1 < m1 ? m1 : ceilf(x1 + 32.f);
      uint32_t pk = pack2(r0, r1);
      const float b0 = blo(pk), b1 = bhi(pk);
      const bool ok0 = fabsf(b0 - r0) <= 8.f, ok1 = fabsf(b1 - r1) <= 8.f;
      if (ok0) r0 = b0;
      if (ok1) r1 = b1;
      const float a0 = ex2(m0 - r0), a1 = ex2(m1 - r1), d0 = r0 - mb0, d1 = r1 - mb1;
      m0 = r0; m1 = r1;
      mb0 = b0; mb1 = b1;
      if (t == 3) {
        pk ^= 0x80008000u;
        qr[NQR * 4 - 2] = __byte_perm(qr[NQR * 4 - 2], pk, 0x5410);
        qr[NQR * 4 - 1] = __byte_perm(qr[NQR * 4 - 1], pk, 0x7610);
      }
      if (dump) {
        if (t == 3) {
          G->meta[o0 * 128 + wg * 64 + wp * 16 + g] = make_float2(om0, o[125]);
          G->meta[o0 * 128 + wg * 64 + wp * 16 + g + 8] = make_float2(om1, o[127]);
        }
        uint8_t* pp = G->part + (size_t)o0 * 65536 + wg * 32768 + tid * 16;
#pragma unroll
        for (int k = 15; k >= 0; k--) {
          if (k == 9 && staged) break;
          stg128(pp + k * 2048, pack2(o[8 * k], o[8 * k + 1]), pack2(o[8 * k + 2], o[8 * k + 3]), pack2(o[8 * k + 4], o[8 * k + 5]), pack2(o[8 * k + 6], o[8 * k + 7]));
        }
        event(2);
        STAMPIF(tid == 0, 14 + wg);
      }
      if (!first && __any_sync(~0u, a0 != 1.f || a1 != 1.f)) {
#pragma unroll
        for (int i = 0; i < 32; i++) { o[4 * i] *= a0; o[4 * i + 1] *= a0; o[4 * i + 2] *= a1; o[4 * i + 3] *= a1; }
      }
#pragma unroll
      for (int i = 0; i < BN / 8; i++) {
        p[2 * i] = pack2(ex2(s[4 * i] - d0), ex2(s[4 * i + 1] - d0));
        p[2 * i + 1] = pack2(ex2(s[4 * i + 2] - d1), ex2(s[4 * i + 3] - d1));
      }
      return (bool)__any_sync(~0u, !(ok0 && ok1));
    };
    {
      int left = n0 + n1 - 1;
      wait_full();
      bar_sync(1 + wg, 256);
      WG_FENCE();
      qk();
      bar_arrive(2 - wg, 256);
      m0 = m1 = -INFINITY;
      mb0 = mb1 = 0.f;
      WG_WAIT(0);
      pin(s);
      GSTAMPIF(threadIdx.x == 0, 8);
      STAMPIF(threadIdx.x == 128, 53);
      bool slow = softmax_slow(false, true);
      STAMPIF(tid == 0, 32 + wg);
      int keep = 0;
      advance();
#pragma unroll 1
      do {
        const bool sw = left == n1;
        wait_full();
        bar_sync(1 + wg, 256);
        WG_FENCE();
        pv(keep);
        keep = !sw;
        if (sw) {
          mbar_wait(qbar, 1);
          slow = true;
#pragma unroll
          for (int i = 0; i < NQR; i++) {
            const int ks = 16 - NQR + i;
            uint32_t f[4];
            ldsm4(f, qw + ((lane >> 3) & 1) * 4096 + (ks >> 2) * 1024 + (lane & 7) * 128 + ((((ks & 3) * 2 + (lane >> 4)) ^ (lane & 7)) << 4));
            qr[4 * i] = f[0]; qr[4 * i + 1] = f[1]; qr[4 * i + 2] = f[2]; qr[4 * i + 3] = f[3];
          }
        }
        WG_FENCE();
        qk();
        bar_arrive(2 - wg, 256);
        WG_WAIT(1);
        release();
        WG_WAIT(0);
        pin(s); pin(o);
        left--;
        if (left == n1 || left == 0) event(left == n1 ? 1 : 6);
        if (!slow) {
          uint32_t acc = 0;
#pragma unroll
          for (int i = 0; i < BN / 4; i++) { p[i] = pack2(ex2(s[2 * i]), ex2(s[2 * i + 1])); acc |= p[i]; }
          slow = __any_sync(~0u, (acc & 0x40004000u) != 0);
        }
        if (slow) {
          GSTAMPIF(threadIdx.x == 0 && sw, 9);
          slow = softmax_slow(sw, sw);
        }
        advance();
      } while (left);
      bar_sync(1 + wg, 256);
      WG_FENCE();
      pv(1);
      bar_arrive(2 - wg, 256);
      WG_WAIT(0);
      pin(o);
      release();
      GSTAMPIF(tid == 0, 10 + wg);
      if (i1 >= 0) {
        mbar_wait(qbar, n1 ? 0 : 1);
        STAMPIF(tid == 0, 18 + wg);
        const uint32_t ma = sb + SM_META + wg * 512 + (wp * 16 + g) * 8;
        float2 h0, h1;
        asm volatile("ld.shared.v2.f32 {%0,%1}, [%2];" : "=f"(h0.x), "=f"(h0.y) : "r"(ma) : "memory");
        asm volatile("ld.shared.v2.f32 {%0,%1}, [%2];" : "=f"(h1.x), "=f"(h1.y) : "r"(ma + 64) : "memory");
#pragma unroll
        for (int k = 0; k < 16; k++) { const uint4 v = lds128(qh + k * 2048 + tid * 16); ga[4 * k] = v.x; ga[4 * k + 1] = v.y; ga[4 * k + 2] = v.z; ga[4 * k + 3] = v.w; }
        if (__any_sync(~0u, h0.x - m0 > 20.f || h1.x - m1 > 20.f)) {
          const float t0 = fmaxf(m0, h0.x), t1 = fmaxf(m1, h1.x), a0 = ex2(m0 - t0), a1 = ex2(m1 - t1);
          m0 = t0; m1 = t1;
#pragma unroll
          for (int i = 0; i < 32; i++) { o[4 * i] *= a0; o[4 * i + 1] *= a0; o[4 * i + 2] *= a1; o[4 * i + 3] *= a1; }
        }
        const float b0 = ex2(h0.x - m0), b1 = ex2(h1.x - m1);
        l0 = fmaf(b0, h0.y, o[125]); l1 = fmaf(b1, h1.y, o[127]);
        const uint32_t bb0 = pack2(b0, b0), bb1 = pack2(b1, b1);
#pragma unroll
        for (int i = 0; i < 64; i++) ga[i] = hfma2(ga[i], (i & 1) ? bb1 : bb0, pack2(o[2 * i], o[2 * i + 1]));
      } else {
        l0 = o[125]; l1 = o[127];
#pragma unroll
        for (int i = 0; i < 64; i++) ga[i] = pack2(o[2 * i], o[2 * i + 1]);
      }
      if (!owner) {
        if (wg) mbar_wait(wsent, 1);
        const int slot = n1 ? q1 : o0;
        uint8_t* pp = G->part + (size_t)slot * 65536 + wg * 32768 + tid * 16;
#pragma unroll
        for (int k = 0; k < 16; k++) stg128(pp + k * 2048, ga[4 * k], ga[4 * k + 1], ga[4 * k + 2], ga[4 * k + 3]);
        if (t == 3) {
          G->meta[slot * 128 + wg * 64 + wp * 16 + g] = make_float2(m0, l0);
          G->meta[slot * 128 + wg * 64 + wp * 16 + g + 8] = make_float2(m1, l1);
        }
        event(3);
        STAMPIF(tid == 0, 16 + wg);
      }
    }

    float f0 = rcp(__shfl_sync(~0u, l0, lane | 3)), f1 = rcp(__shfl_sync(~0u, l1, lane | 3));
#pragma unroll 1
    for (int rnd = 0;; rnd++) {
      int r0 = q0 * 128 + wg * 64;
      if (!owner) {
        r0 = (rnd ? lu2 : lu + wg) * 64;
        mbar_wait(xbar0 + 8 * (rnd * 2 + wg), 1);
        const uint32_t la = (rnd || role == 4 ? sb + SM_AUX + wp * 8192 : qw) + g * 512 + t * 16;
#pragma unroll
        for (int J = 0; J < 8; J++) {
          const uint4 va = lds128(la + J * 64), vb = lds128(la + 4096 + J * 64);
          ga[8 * J] = va.x; ga[8 * J + 1] = vb.x; ga[8 * J + 2] = va.y; ga[8 * J + 3] = vb.y;
          ga[8 * J + 4] = va.z; ga[8 * J + 5] = vb.z; ga[8 * J + 6] = va.w; ga[8 * J + 7] = vb.w;
        }
        uint32_t d0, d1;
        asm volatile("ld.shared.u16 %0, [%1];" : "=r"(d0) : "r"(sb + SM_DINV + (rnd * 128 + wg * 64 + wp * 16 + g) * 2) : "memory");
        asm volatile("ld.shared.u16 %0, [%1];" : "=r"(d1) : "r"(sb + SM_DINV + (rnd * 128 + wg * 64 + wp * 16 + g + 8) * 2) : "memory");
        f0 = blo(d0); f1 = blo(d1);
        if (rnd == 0) event(5);
      }
      r0 += wp * 16;
#pragma unroll
      for (int i = 0; i < 64; i++) asm volatile("" : "+r"(ga[i])::"memory");
      STAMPIF(tid == 0, 47 + wg);
      bar_sync(1 + wg, 256);
#pragma unroll
      for (int c = 0; c < 3; c++) {
        if (rnd == 0) wait_full();
        WG_FENCE();
        const uint32_t wd = vd0 + st * (STB >> 4);
#pragma unroll
        for (int k = 0; k < 5; k++) { const int ks = c * 5 + k; wgmma_rs256(o, ga[ks * 4], ga[ks * 4 + 1], ga[ks * 4 + 2], ga[ks * 4 + 3], wd + k * 512, ks != 0); }
        if (c == 2) wgmma_rs256(o, ga[60], ga[61], ga[62], ga[63], rd, 1);
        WG_COMMIT();
        advance();
      }
      if (wg == 0 ? rnd == 0 : n1 != 0) bar_arrive(2 - wg, 256);
      BULK_WAIT_READ();
      __syncwarp();
      WG_WAIT(0);
      pin(o);
      STAMPIF(tid == 0, 20 + wg);
      const uint32_t ap = qw + g * 512 + t * 16 + ((g & 1) << 6);
      const bool odd = g & 1;
#pragma unroll
      for (int h = 0; h < 2; h++) {
        const float f = h ? f1 : f0;
#pragma unroll
        for (int J = 0; J < 8; J += 2) {
          uint32_t y[8];
#pragma unroll
          for (int i = 0; i < 8; i++) y[i] = pack2(o[16 * J + 4 * i + 2 * h] * f, o[16 * J + 4 * i + 2 * h + 1] * f);
          sts128(ap + h * 4096 + J * 64, odd ? y[4] : y[0], odd ? y[5] : y[1], odd ? y[6] : y[2], odd ? y[7] : y[3]);
          sts128((ap ^ 64) + h * 4096 + J * 64, odd ? y[0] : y[4], odd ? y[1] : y[5], odd ? y[2] : y[6], odd ? y[3] : y[7]);
        }
        PROXY_FENCE_SMEM();
        __syncwarp();
        if (lane == 0 && r0 < N_) { bulk_red((uint8_t*)out + (size_t)r0 * 512 + h * 4096, qw + h * 4096, 4096); BULK_COMMIT(); }
      }
      STAMPIF(tid == 0, 51 + wg);
      if (rnd || wg || !n1) break;
    }
    BULK_WAIT_READ();
    GSTAMPIF(tid == 0, 22 + wg);
    PROF_DUMP();
  }
}

}

extern "C" void kernel_launch(void* const* d_in, const int* in_sizes, int n_in, void* d_out, int out_size) {
  (void)in_sizes; (void)n_in; (void)out_size;
  void* scratch = nullptr;
  cudaGetSymbolAddress(&scratch, g_scratch);
  cudaFuncSetAttribute(gps_kernel, cudaFuncAttributeMaxDynamicSharedMemorySize, SM_TOTAL);
  gps_kernel<<<NCTA, 384, SM_TOTAL>>>((const __nv_bfloat16*)d_in[0], (const int*)d_in[1], (const int*)d_in[2],
                                      (const __nv_bfloat16*)d_in[3], (const __nv_bfloat16*)d_in[4], (const __nv_bfloat16*)d_in[5],
                                      (const __nv_bfloat16*)d_in[6], (const __nv_bfloat16*)d_in[7], (const __nv_bfloat16*)d_in[8],
                                      (__nv_bfloat16*)d_out, (Scratch*)scratch);
}
```

```cpp
#include <cuda_runtime.h>
#include <cuda_bf16.h>
#include <stdint.h>

namespace {

constexpr int N_ = 10000, E_ = 160000, NQT = 79, NPAD = NQT * 128;
constexpr int BN = 80, NKV = 125, NST = 3, STB = BN * 512, NCTA = 132;
constexpr int NSLOT = NQT + 26;
#define SCHED_A 76
#define SCHED_B 76
#define SCHED_C 76
#define SCHED_B1 25
#define NQR 1
#define EREL 0
#define HSPLIT 16384
#define JBG 5
#define JSCAT 45
constexpr int SM_Q = 0, SM_RING = 65536, SM_REM = SM_RING + NST * STB, SM_AUX = SM_REM + 8192, SM_META = SM_AUX + 32768;
constexpr int SM_BAR = SM_META + 1024, SM_DINV = SM_BAR + 1280, SM_TOTAL = SM_BAR + 1792;
constexpr unsigned CNT_W = 64, CNT_H = NCTA, CNT_E = 5, CNT_F = 4, CNT_M = NCTA + 64, CNT_G = NCTA * 2;
constexpr int C_W = 0, C_H = 32, C_E = 64, C_M = 96, C_G = 128, C_F = 160;

struct Scratch {
  unsigned ctr[6 * 32], epoch, pad0[31], pflag[NSLOT * 2], pad1[1024 - 7 * 32 - NSLOT * 2];
  uint8_t w[3 * 131072];
  float2 meta[NSLOT * 128];
  uint8_t ht[NPAD * 512];
  uint8_t qt[NPAD * 512];
  uint8_t acc[NCTA * 40960];
  uint8_t part[NSLOT * 65536];
  unsigned box[NCTA * NKV * 32];
  int ovf[NCTA * 1280];
};
__device__ __align__(1024) Scratch g_scratch;
#define STAMPIF(c, i)
#define GSTAMPIF(c, i)
#define PROF_DUMP()

constexpr uint32_t DESC_HI = 0x40000100u;
__device__ __forceinline__ void wgmma_qk64(float (&d)[40], uint64_t da, uint64_t db, int sd) {
  asm volatile("{\n.reg .pred p;\nsetp.ne.b32 p, %42, 0;\n"
    "wgmma.mma_async.sync.aligned.m64n80k16.f32.bf16.bf16 {%0, %1, %2, %3, %4, %5, %6, %7, %8, %9, %10, %11, %12, %13, %14, %15, %16, %17, %18, %19, %20, %21, %22, %23, %24, %25, %26, %27, %28, %29, %30, %31, %32, %33, %34, %35, %36, %37, %38, %39}, %40, %41, p, 1, 1, 0, 0;\n}\n"
    : "+f"(d[0]), "+f"(d[1]), "+f"(d[2]), "+f"(d[3]), "+f"(d[4]), "+f"(d[5]), "+f"(d[6]), "+f"(d[7]), "+f"(d[8]), "+f"(d[9]), "+f"(d[10]), "+f"(d[11]), "+f"(d[12]), "+f"(d[13]), "+f"(d[14]), "+f"(d[15]), "+f"(d[16]), "+f"(d[17]), "+f"(d[18]), "+f"(d[19]), "+f"(d[20]), "+f"(d[21]), "+f"(d[22]), "+f"(d[23]), "+f"(d[24]), "+f"(d[25]), "+f"(d[26]), "+f"(d[27]), "+f"(d[28]), "+f"(d[29]), "+f"(d[30]), "+f"(d[31]), "+f"(d[32]), "+f"(d[33]), "+f"(d[34]), "+f"(d[35]), "+f"(d[36]), "+f"(d[37]), "+f"(d[38]), "+f"(d[39])
    : "l"(da), "l"(db), "r"(sd));
}

__device__ __forceinline__ void wgmma_qkr64(float (&d)[40], uint32_t a0, uint32_t a1, uint32_t a2, uint32_t a3, uint64_t db, int sd) {
  asm volatile("{\n.reg .pred p;\nsetp.ne.b32 p, %45, 0;\n"
    "wgmma.mma_async.sync.aligned.m64n80k16.f32.bf16.bf16 {%0, %1, %2, %3, %4, %5, %6, %7, %8, %9, %10, %11, %12, %13, %14, %15, %16, %17, %18, %19, %20, %21, %22, %23, %24, %25, %26, %27, %28, %29, %30, %31, %32, %33, %34, %35, %36, %37, %38, %39}, {%40, %41, %42, %43}, %44, p, 1, 1, 0;\n}\n"
    : "+f"(d[0]), "+f"(d[1]), "+f"(d[2]), "+f"(d[3]), "+f"(d[4]), "+f"(d[5]), "+f"(d[6]), "+f"(d[7]), "+f"(d[8]), "+f"(d[9]), "+f"(d[10]), "+f"(d[11]), "+f"(d[12]), "+f"(d[13]), "+f"(d[14]), "+f"(d[15]), "+f"(d[16]), "+f"(d[17]), "+f"(d[18]), "+f"(d[19]), "+f"(d[20]), "+f"(d[21]), "+f"(d[22]), "+f"(d[23]), "+f"(d[24]), "+f"(d[25]), "+f"(d[26]), "+f"(d[27]), "+f"(d[28]), "+f"(d[29]), "+f"(d[30]), "+f"(d[31]), "+f"(d[32]), "+f"(d[33]), "+f"(d[34]), "+f"(d[35]), "+f"(d[36]), "+f"(d[37]), "+f"(d[38]), "+f"(d[39])
    : "r"(a0), "r"(a1), "r"(a2), "r"(a3), "l"(db), "r"(sd));
}

__device__ __forceinline__ void wgmma_pv64(float (&d)[128], uint32_t a0, uint32_t a1, uint32_t a2, uint32_t a3, uint64_t db, int sd) {
  asm volatile("{\n.reg .pred p;\nsetp.ne.b32 p, %133, 0;\n"
    "wgmma.mma_async.sync.aligned.m64n256k16.f32.bf16.bf16 {%0, %1, %2, %3, %4, %5, %6, %7, %8, %9, %10, %11, %12, %13, %14, %15, %16, %17, %18, %19, %20, %21, %22, %23, %24, %25, %26, %27, %28, %29, %30, %31, %32, %33, %34, %35, %36, %37, %38, %39, %40, %41, %42, %43, %44, %45, %46, %47, %48, %49, %50, %51, %52, %53, %54, %55, %56, %57, %58, %59, %60, %61, %62, %63, %64, %65, %66, %67, %68, %69, %70, %71, %72, %73, %74, %75, %76, %77, %78, %79, %80, %81, %82, %83, %84, %85, %86, %87, %88, %89, %90, %91, %92, %93, %94, %95, %96, %97, %98, %99, %100, %101, %102, %103, %104, %105, %106, %107, %108, %109, %110, %111, %112, %113, %114, %115, %116, %117, %118, %119, %120, %121, %122, %123, %124, %125, %126, %127}, {%128, %129, %130, %131}, %132, p, 1, 1, 1;\n}\n"
    : "+f"(d[0]), "+f"(d[1]), "+f"(d[2]), "+f"(d[3]), "+f"(d[4]), "+f"(d[5]), "+f"(d[6]), "+f"(d[7]), "+f"(d[8]), "+f"(d[9]), "+f"(d[10]), "+f"(d[11]), "+f"(d[12]), "+f"(d[13]), "+f"(d[14]), "+f"(d[15]), "+f"(d[16]), "+f"(d[17]), "+f"(d[18]), "+f"(d[19]), "+f"(d[20]), "+f"(d[21]), "+f"(d[22]), "+f"(d[23]), "+f"(d[24]), "+f"(d[25]), "+f"(d[26]), "+f"(d[27]), "+f"(d[28]), "+f"(d[29]), "+f"(d[30]), "+f"(d[31]), "+f"(d[32]), "+f"(d[33]), "+f"(d[34]), "+f"(d[35]), "+f"(d[36]), "+f"(d[37]), "+f"(d[38]), "+f"(d[39]), "+f"(d[40]), "+f"(d[41]), "+f"(d[42]), "+f"(d[43]), "+f"(d[44]), "+f"(d[45]), "+f"(d[46]), "+f"(d[47]), "+f"(d[48]), "+f"(d[49]), "+f"(d[50]), "+f"(d[51]), "+f"(d[52]), "+f"(d[53]), "+f"(d[54]), "+f"(d[55]), "+f"(d[56]), "+f"(d[57]), "+f"(d[58]), "+f"(d[59]), "+f"(d[60]), "+f"(d[61]), "+f"(d[62]), "+f"(d[63]), "+f"(d[64]), "+f"(d[65]), "+f"(d[66]), "+f"(d[67]), "+f"(d[68]), "+f"(d[69]), "+f"(d[70]), "+f"(d[71]), "+f"(d[72]), "+f"(d[73]), "+f"(d[74]), "+f"(d[75]), "+f"(d[76]), "+f"(d[77]), "+f"(d[78]), "+f"(d[79]), "+f"(d[80]), "+f"(d[81]), "+f"(d[82]), "+f"(d[83]), "+f"(d[84]), "+f"(d[85]), "+f"(d[86]), "+f"(d[87]), "+f"(d[88]), "+f"(d[89]), "+f"(d[90]), "+f"(d[91]), "+f"(d[92]), "+f"(d[93]), "+f"(d[94]), "+f"(d[95]), "+f"(d[96]), "+f"(d[97]), "+f"(d[98]), "+f"(d[99]), "+f"(d[100]), "+f"(d[101]), "+f"(d[102]), "+f"(d[103]), "+f"(d[104]), "+f"(d[105]), "+f"(d[106]), "+f"(d[107]), "+f"(d[108]), "+f"(d[109]), "+f"(d[110]), "+f"(d[111]), "+f"(d[112]), "+f"(d[113]), "+f"(d[114]), "+f"(d[115]), "+f"(d[116]), "+f"(d[117]), "+f"(d[118]), "+f"(d[119]), "+f"(d[120]), "+f"(d[121]), "+f"(d[122]), "+f"(d[123]), "+f"(d[124]), "+f"(d[125]), "+f"(d[126]), "+f"(d[127])
    : "r"(a0), "r"(a1), "r"(a2), "r"(a3), "l"(db), "r"(sd));
}

__device__ __forceinline__ void wgmma_qk(float (&d)[40], uint32_t da, uint32_t db, int sd) {
  asm volatile("{\n.reg .pred p;\n.reg .b64 da, db;\nmov.b64 da, {%40, %43};\nmov.b64 db, {%41, %43};\nsetp.ne.b32 p, %42, 0;\n"
    "wgmma.mma_async.sync.aligned.m64n80k16.f32.bf16.bf16 {%0, %1, %2, %3, %4, %5, %6, %7, %8, %9, %10, %11, %12, %13, %14, %15, %16, %17, %18, %19, %20, %21, %22, %23, %24, %25, %26, %27, %28, %29, %30, %31, %32, %33, %34, %35, %36, %37, %38, %39}, da, db, p, 1, 1, 0, 0;\n}\n"
    : "+f"(d[0]), "+f"(d[1]), "+f"(d[2]), "+f"(d[3]), "+f"(d[4]), "+f"(d[5]), "+f"(d[6]), "+f"(d[7]), "+f"(d[8]), "+f"(d[9]), "+f"(d[10]), "+f"(d[11]), "+f"(d[12]), "+f"(d[13]), "+f"(d[14]), "+f"(d[15]), "+f"(d[16]), "+f"(d[17]), "+f"(d[18]), "+f"(d[19]), "+f"(d[20]), "+f"(d[21]), "+f"(d[22]), "+f"(d[23]), "+f"(d[24]), "+f"(d[25]), "+f"(d[26]), "+f"(d[27]), "+f"(d[28]), "+f"(d[29]), "+f"(d[30]), "+f"(d[31]), "+f"(d[32]), "+f"(d[33]), "+f"(d[34]), "+f"(d[35]), "+f"(d[36]), "+f"(d[37]), "+f"(d[38]), "+f"(d[39])
    : "r"(da), "r"(db), "r"(sd), "r"(DESC_HI));
}

__device__ __forceinline__ void wgmma_rs256(float (&d)[128], uint32_t a0, uint32_t a1, uint32_t a2, uint32_t a3, uint32_t db, int sd) {
  asm volatile("{\n.reg .pred p;\n.reg .b64 da, db;\nmov.b64 db, {%132, %134};\nsetp.ne.b32 p, %133, 0;\n"
    "wgmma.mma_async.sync.aligned.m64n256k16.f32.bf16.bf16 {%0, %1, %2, %3, %4, %5, %6, %7, %8, %9, %10, %11, %12, %13, %14, %15, %16, %17, %18, %19, %20, %21, %22, %23, %24, %25, %26, %27, %28, %29, %30, %31, %32, %33, %34, %35, %36, %37, %38, %39, %40, %41, %42, %43, %44, %45, %46, %47, %48, %49, %50, %51, %52, %53, %54, %55, %56, %57, %58, %59, %60, %61, %62, %63, %64, %65, %66, %67, %68, %69, %70, %71, %72, %73, %74, %75, %76, %77, %78, %79, %80, %81, %82, %83, %84, %85, %86, %87, %88, %89, %90, %91, %92, %93, %94, %95, %96, %97, %98, %99, %100, %101, %102, %103, %104, %105, %106, %107, %108, %109, %110, %111, %112, %113, %114, %115, %116, %117, %118, %119, %120, %121, %122, %123, %124, %125, %126, %127}, {%128, %129, %130, %131}, db, p, 1, 1, 1;\n}\n"
    : "+f"(d[0]), "+f"(d[1]), "+f"(d[2]), "+f"(d[3]), "+f"(d[4]), "+f"(d[5]), "+f"(d[6]), "+f"(d[7]), "+f"(d[8]), "+f"(d[9]), "+f"(d[10]), "+f"(d[11]), "+f"(d[12]), "+f"(d[13]), "+f"(d[14]), "+f"(d[15]), "+f"(d[16]), "+f"(d[17]), "+f"(d[18]), "+f"(d[19]), "+f"(d[20]), "+f"(d[21]), "+f"(d[22]), "+f"(d[23]), "+f"(d[24]), "+f"(d[25]), "+f"(d[26]), "+f"(d[27]), "+f"(d[28]), "+f"(d[29]), "+f"(d[30]), "+f"(d[31]), "+f"(d[32]), "+f"(d[33]), "+f"(d[34]), "+f"(d[35]), "+f"(d[36]), "+f"(d[37]), "+f"(d[38]), "+f"(d[39]), "+f"(d[40]), "+f"(d[41]), "+f"(d[42]), "+f"(d[43]), "+f"(d[44]), "+f"(d[45]), "+f"(d[46]), "+f"(d[47]), "+f"(d[48]), "+f"(d[49]), "+f"(d[50]), "+f"(d[51]), "+f"(d[52]), "+f"(d[53]), "+f"(d[54]), "+f"(d[55]), "+f"(d[56]), "+f"(d[57]), "+f"(d[58]), "+f"(d[59]), "+f"(d[60]), "+f"(d[61]), "+f"(d[62]), "+f"(d[63]), "+f"(d[64]), "+f"(d[65]), "+f"(d[66]), "+f"(d[67]), "+f"(d[68]), "+f"(d[69]), "+f"(d[70]), "+f"(d[71]), "+f"(d[72]), "+f"(d[73]), "+f"(d[74]), "+f"(d[75]), "+f"(d[76]), "+f"(d[77]), "+f"(d[78]), "+f"(d[79]), "+f"(d[80]), "+f"(d[81]), "+f"(d[82]), "+f"(d[83]), "+f"(d[84]), "+f"(d[85]), "+f"(d[86]), "+f"(d[87]), "+f"(d[88]), "+f"(d[89]), "+f"(d[90]), "+f"(d[91]), "+f"(d[92]), "+f"(d[93]), "+f"(d[94]), "+f"(d[95]), "+f"(d[96]), "+f"(d[97]), "+f"(d[98]), "+f"(d[99]), "+f"(d[100]), "+f"(d[101]), "+f"(d[102]), "+f"(d[103]), "+f"(d[104]), "+f"(d[105]), "+f"(d[106]), "+f"(d[107]), "+f"(d[108]), "+f"(d[109]), "+f"(d[110]), "+f"(d[111]), "+f"(d[112]), "+f"(d[113]), "+f"(d[114]), "+f"(d[115]), "+f"(d[116]), "+f"(d[117]), "+f"(d[118]), "+f"(d[119]), "+f"(d[120]), "+f"(d[121]), "+f"(d[122]), "+f"(d[123]), "+f"(d[124]), "+f"(d[125]), "+f"(d[126]), "+f"(d[127])
    : "r"(a0), "r"(a1), "r"(a2), "r"(a3), "r"(db), "r"(sd), "r"(DESC_HI));
}

__device__ __forceinline__ void wgmma_ss256(float (&d)[128], uint32_t da, uint32_t db, int sd) {
  asm volatile("{\n.reg .pred p;\n.reg .b64 da, db;\nmov.b64 da, {%128, %131};\nmov.b64 db, {%129, %131};\nsetp.ne.b32 p, %130, 0;\n"
    "wgmma.mma_async.sync.aligned.m64n256k16.f32.bf16.bf16 {%0, %1, %2, %3, %4, %5, %6, %7, %8, %9, %10, %11, %12, %13, %14, %15, %16, %17, %18, %19, %20, %21, %22, %23, %24, %25, %26, %27, %28, %29, %30, %31, %32, %33, %34, %35, %36, %37, %38, %39, %40, %41, %42, %43, %44, %45, %46, %47, %48, %49, %50, %51, %52, %53, %54, %55, %56, %57, %58, %59, %60, %61, %62, %63, %64, %65, %66, %67, %68, %69, %70, %71, %72, %73, %74, %75, %76, %77, %78, %79, %80, %81, %82, %83, %84, %85, %86, %87, %88, %89, %90, %91, %92, %93, %94, %95, %96, %97, %98, %99, %100, %101, %102, %103, %104, %105, %106, %107, %108, %109, %110, %111, %112, %113, %114, %115, %116, %117, %118, %119, %120, %121, %122, %123, %124, %125, %126, %127}, da, db, p, 1, 1, 0, 1;\n}\n"
    : "+f"(d[0]), "+f"(d[1]), "+f"(d[2]), "+f"(d[3]), "+f"(d[4]), "+f"(d[5]), "+f"(d[6]), "+f"(d[7]), "+f"(d[8]), "+f"(d[9]), "+f"(d[10]), "+f"(d[11]), "+f"(d[12]), "+f"(d[13]), "+f"(d[14]), "+f"(d[15]), "+f"(d[16]), "+f"(d[17]), "+f"(d[18]), "+f"(d[19]), "+f"(d[20]), "+f"(d[21]), "+f"(d[22]), "+f"(d[23]), "+f"(d[24]), "+f"(d[25]), "+f"(d[26]), "+f"(d[27]), "+f"(d[28]), "+f"(d[29]), "+f"(d[30]), "+f"(d[31]), "+f"(d[32]), "+f"(d[33]), "+f"(d[34]), "+f"(d[35]), "+f"(d[36]), "+f"(d[37]), "+f"(d[38]), "+f"(d[39]), "+f"(d[40]), "+f"(d[41]), "+f"(d[42]), "+f"(d[43]), "+f"(d[44]), "+f"(d[45]), "+f"(d[46]), "+f"(d[47]), "+f"(d[48]), "+f"(d[49]), "+f"(d[50]), "+f"(d[51]), "+f"(d[52]), "+f"(d[53]), "+f"(d[54]), "+f"(d[55]), "+f"(d[56]), "+f"(d[57]), "+f"(d[58]), "+f"(d[59]), "+f"(d[60]), "+f"(d[61]), "+f"(d[62]), "+f"(d[63]), "+f"(d[64]), "+f"(d[65]), "+f"(d[66]), "+f"(d[67]), "+f"(d[68]), "+f"(d[69]), "+f"(d[70]), "+f"(d[71]), "+f"(d[72]), "+f"(d[73]), "+f"(d[74]), "+f"(d[75]), "+f"(d[76]), "+f"(d[77]), "+f"(d[78]), "+f"(d[79]), "+f"(d[80]), "+f"(d[81]), "+f"(d[82]), "+f"(d[83]), "+f"(d[84]), "+f"(d[85]), "+f"(d[86]), "+f"(d[87]), "+f"(d[88]), "+f"(d[89]), "+f"(d[90]), "+f"(d[91]), "+f"(d[92]), "+f"(d[93]), "+f"(d[94]), "+f"(d[95]), "+f"(d[96]), "+f"(d[97]), "+f"(d[98]), "+f"(d[99]), "+f"(d[100]), "+f"(d[101]), "+f"(d[102]), "+f"(d[103]), "+f"(d[104]), "+f"(d[105]), "+f"(d[106]), "+f"(d[107]), "+f"(d[108]), "+f"(d[109]), "+f"(d[110]), "+f"(d[111]), "+f"(d[112]), "+f"(d[113]), "+f"(d[114]), "+f"(d[115]), "+f"(d[116]), "+f"(d[117]), "+f"(d[118]), "+f"(d[119]), "+f"(d[120]), "+f"(d[121]), "+f"(d[122]), "+f"(d[123]), "+f"(d[124]), "+f"(d[125]), "+f"(d[126]), "+f"(d[127])
    : "r"(da), "r"(db), "r"(sd), "r"(DESC_HI));
}

__device__ __forceinline__ void wgmma_qkr(float (&d)[40], uint32_t a0, uint32_t a1, uint32_t a2, uint32_t a3, uint32_t db, int sd) {
  asm volatile("{\n.reg .pred p;\n.reg .b64 da, db;\nmov.b64 db, {%44, %46};\nsetp.ne.b32 p, %45, 0;\n"
    "wgmma.mma_async.sync.aligned.m64n80k16.f32.bf16.bf16 {%0, %1, %2, %3, %4, %5, %6, %7, %8, %9, %10, %11, %12, %13, %14, %15, %16, %17, %18, %19, %20, %21, %22, %23, %24, %25, %26, %27, %28, %29, %30, %31, %32, %33, %34, %35, %36, %37, %38, %39}, {%40, %41, %42, %43}, db, p, 1, 1, 0;\n}\n"
    : "+f"(d[0]), "+f"(d[1]), "+f"(d[2]), "+f"(d[3]), "+f"(d[4]), "+f"(d[5]), "+f"(d[6]), "+f"(d[7]), "+f"(d[8]), "+f"(d[9]), "+f"(d[10]), "+f"(d[11]), "+f"(d[12]), "+f"(d[13]), "+f"(d[14]), "+f"(d[15]), "+f"(d[16]), "+f"(d[17]), "+f"(d[18]), "+f"(d[19]), "+f"(d[20]), "+f"(d[21]), "+f"(d[22]), "+f"(d[23]), "+f"(d[24]), "+f"(d[25]), "+f"(d[26]), "+f"(d[27]), "+f"(d[28]), "+f"(d[29]), "+f"(d[30]), "+f"(d[31]), "+f"(d[32]), "+f"(d[33]), "+f"(d[34]), "+f"(d[35]), "+f"(d[36]), "+f"(d[37]), "+f"(d[38]), "+f"(d[39])
    : "r"(a0), "r"(a1), "r"(a2), "r"(a3), "r"(db), "r"(sd), "r"(DESC_HI));
}

__device__ __forceinline__ void wgmma_rs40(float (&d)[20], uint32_t a0, uint32_t a1, uint32_t a2, uint32_t a3, uint32_t db, int sd) {
  asm volatile("{\n.reg .pred p;\n.reg .b64 da, db;\nmov.b64 db, {%24, %26};\nsetp.ne.b32 p, %25, 0;\n"
    "wgmma.mma_async.sync.aligned.m64n40k16.f32.bf16.bf16 {%0, %1, %2, %3, %4, %5, %6, %7, %8, %9, %10, %11, %12, %13, %14, %15, %16, %17, %18, %19}, {%20, %21, %22, %23}, db, p, 1, 1, 0;\n}\n"
    : "+f"(d[0]), "+f"(d[1]), "+f"(d[2]), "+f"(d[3]), "+f"(d[4]), "+f"(d[5]), "+f"(d[6]), "+f"(d[7]), "+f"(d[8]), "+f"(d[9]), "+f"(d[10]), "+f"(d[11]), "+f"(d[12]), "+f"(d[13]), "+f"(d[14]), "+f"(d[15]), "+f"(d[16]), "+f"(d[17]), "+f"(d[18]), "+f"(d[19])
    : "r"(a0), "r"(a1), "r"(a2), "r"(a3), "r"(db), "r"(sd), "r"(DESC_HI));
}

__device__ __forceinline__ void wgmma_rs64t(float (&d)[32], uint32_t a0, uint32_t a1, uint32_t a2, uint32_t a3, uint32_t db, int sd) {
  asm volatile("{\n.reg .pred p;\n.reg .b64 da, db;\nmov.b64 db, {%36, %38};\nsetp.ne.b32 p, %37, 0;\n"
    "wgmma.mma_async.sync.aligned.m64n64k16.f32.bf16.bf16 {%0, %1, %2, %3, %4, %5, %6, %7, %8, %9, %10, %11, %12, %13, %14, %15, %16, %17, %18, %19, %20, %21, %22, %23, %24, %25, %26, %27, %28, %29, %30, %31}, {%32, %33, %34, %35}, db, p, 1, 1, 1;\n}\n"
    : "+f"(d[0]), "+f"(d[1]), "+f"(d[2]), "+f"(d[3]), "+f"(d[4]), "+f"(d[5]), "+f"(d[6]), "+f"(d[7]), "+f"(d[8]), "+f"(d[9]), "+f"(d[10]), "+f"(d[11]), "+f"(d[12]), "+f"(d[13]), "+f"(d[14]), "+f"(d[15]), "+f"(d[16]), "+f"(d[17]), "+f"(d[18]), "+f"(d[19]), "+f"(d[20]), "+f"(d[21]), "+f"(d[22]), "+f"(d[23]), "+f"(d[24]), "+f"(d[25]), "+f"(d[26]), "+f"(d[27]), "+f"(d[28]), "+f"(d[29]), "+f"(d[30]), "+f"(d[31])
    : "r"(a0), "r"(a1), "r"(a2), "r"(a3), "r"(db), "r"(sd), "r"(0x40000040u));
}

__device__ __forceinline__ uint32_t mkdesc(uint32_t addr, uint32_t lbo) { return ((addr & 0x3FFFF) >> 4) | ((lbo >> 4) << 16); }
#define WG_FENCE() asm volatile("wgmma.fence.sync.aligned;\n" ::: "memory")
#define WG_COMMIT() asm volatile("wgmma.commit_group.sync.aligned;\n" ::: "memory")
#define WG_WAIT(n) asm volatile("wgmma.wait_group.sync.aligned %0;\n" ::"n"(n) : "memory")
template <int N> __device__ __forceinline__ void pin(float (&d)[N]) {
#pragma unroll
  for (int i = 0; i < N; i++) asm volatile("" : "+f"(d[i])::"memory");
}
#define PROXY_FENCE() asm volatile("fence.proxy.async;\n" ::: "memory")
#define PROXY_FENCE_SMEM() asm volatile("fence.proxy.async.shared::cta;\n" ::: "memory")

__device__ __forceinline__ void mbar_init(uint32_t bar, uint32_t cnt) { asm volatile("mbarrier.init.shared::cta.b64 [%0], %1;\n" ::"r"(bar), "r"(cnt) : "memory"); }
__device__ __forceinline__ void mbar_expect_tx(uint32_t bar, uint32_t bytes) { asm volatile("mbarrier.arrive.expect_tx.shared::cta.b64 _, [%0], %1;\n" ::"r"(bar), "r"(bytes) : "memory"); }
__device__ __forceinline__ void mbar_arrive(uint32_t bar) { asm volatile("mbarrier.arrive.shared::cta.b64 _, [%0];\n" ::"r"(bar) : "memory"); }
__device__ __forceinline__ void mbar_wait(uint32_t bar, uint32_t parity) {
  asm volatile("{\n.reg .pred p;\n.reg .u32 n;\n.reg .u64 z;\nmov.u64 z, 0;\nmov.u32 n, 0;\n"
               "LAB_WAIT:\n"
               "mbarrier.try_wait.parity.shared::cta.b64 p, [%0], %1;\n"
               "@p bra LAB_DONE;\n"
               "add.u32 n, n, 1;\n"
               "setp.gt.u32 p, n, 100000000;\n"
               "@p st.global.u32 [z], n;\n"
               "bra LAB_WAIT;\n"
               "LAB_DONE:\n}\n" ::"r"(bar), "r"(parity) : "memory");
}
__device__ __forceinline__ void gwait(const unsigned* p, unsigned target) {
  asm volatile("{\n.reg .pred p;\n.reg .u32 n, v;\n.reg .u64 z;\nmov.u64 z, 0;\nmov.u32 n, 0;\n"
               "LAB_WAIT:\n"
               "ld.acquire.gpu.global.u32 v, [%0];\n"
               "sub.u32 v, v, %1;\n"
               "setp.ge.s32 p, v, 0;\n"
               "@p bra LAB_DONE;\n"
               "add.u32 n, n, 1;\n"
               "setp.gt.u32 p, n, 20000000;\n"
               "@p st.global.u32 [z], n;\n"
               "bra LAB_WAIT;\n"
               "LAB_DONE:\n}\n" ::"l"(p), "r"(target) : "memory");
}
#define GPU_FENCE() asm volatile("fence.acq_rel.gpu;\n" ::: "memory")
__device__ __forceinline__ void garrive(unsigned* p) { asm volatile("red.release.gpu.global.add.u32 [%0], 1;\n" ::"l"(p) : "memory"); }
__device__ __forceinline__ void garrive_relaxed(unsigned* p) { asm volatile("red.relaxed.gpu.global.add.u32 [%0], 1;\n" ::"l"(p) : "memory"); }
__device__ __forceinline__ void gset(unsigned* p, unsigned v) { asm volatile("st.release.gpu.global.u32 [%0], %1;\n" ::"l"(p), "r"(v) : "memory"); }
__device__ __forceinline__ void bulk_g2s(uint32_t dst, const void* src, uint32_t bytes, uint32_t bar) {
  asm volatile("cp.async.bulk.shared::cluster.global.mbarrier::complete_tx::bytes [%0], [%1], %2, [%3];\n" ::"r"(dst), "l"(src), "r"(bytes), "r"(bar) : "memory");
}
__device__ __forceinline__ void bar_sync(int id, int n) { asm volatile("bar.sync %0, %1;\n" ::"r"(id), "r"(n) : "memory"); }
__device__ __forceinline__ void bar_arrive(int id, int n) { asm volatile("bar.arrive %0, %1;\n" ::"r"(id), "r"(n) : "memory"); }
__device__ __forceinline__ float ex2(float x) { float y; asm("ex2.approx.ftz.f32 %0, %1;" : "=f"(y) : "f"(x)); return y; }
__device__ __forceinline__ float rcp(float x) { float y; asm volatile("rcp.approx.ftz.f32 %0, %1;" : "=f"(y) : "f"(x)); return y; }
__device__ __forceinline__ float rsq(float x) { float y; asm("rsqrt.approx.ftz.f32 %0, %1;" : "=f"(y) : "f"(x)); return y; }
__device__ __forceinline__ uint32_t pack2(float lo, float hi) { uint32_t r; asm("cvt.rn.bf16x2.f32 %0, %1, %2;" : "=r"(r) : "f"(hi), "f"(lo)); return r; }
__device__ __forceinline__ float blo(uint32_t v) { return __uint_as_float(v << 16); }
__device__ __forceinline__ float bhi(uint32_t v) { return __uint_as_float(v & 0xffff0000u); }
__device__ __forceinline__ uint4 ldg_nc(const void* p) { uint4 v; asm volatile("ld.global.nc.v4.u32 {%0,%1,%2,%3}, [%4];" : "=r"(v.x), "=r"(v.y), "=r"(v.z), "=r"(v.w) : "l"(p)); return v; }
__device__ __forceinline__ uint4 ldg_cg(const void* p) { uint4 v; asm volatile("ld.global.cg.v4.u32 {%0,%1,%2,%3}, [%4];" : "=r"(v.x), "=r"(v.y), "=r"(v.z), "=r"(v.w) : "l"(p) : "memory"); return v; }
__device__ __forceinline__ void stg128(void* p, uint32_t a, uint32_t b, uint32_t c, uint32_t d) { asm volatile("st.global.v4.u32 [%0], {%1,%2,%3,%4};" ::"l"(p), "r"(a), "r"(b), "r"(c), "r"(d) : "memory"); }
__device__ __forceinline__ void sts128(uint32_t p, uint32_t a, uint32_t b, uint32_t c, uint32_t d) { asm volatile("st.shared.v4.u32 [%0], {%1,%2,%3,%4};" ::"r"(p), "r"(a), "r"(b), "r"(c), "r"(d) : "memory"); }
__device__ __forceinline__ uint4 lds128(uint32_t p) { uint4 v; asm volatile("ld.shared.v4.u32 {%0,%1,%2,%3}, [%4];" : "=r"(v.x), "=r"(v.y), "=r"(v.z), "=r"(v.w) : "r"(p) : "memory"); return v; }
__device__ __forceinline__ float quad_sum(float v) { v += __shfl_xor_sync(~0u, v, 1); return v + __shfl_xor_sync(~0u, v, 2); }
__device__ __forceinline__ float quad_max(float v) { v = fmaxf(v, __shfl_xor_sync(~0u, v, 1)); return fmaxf(v, __shfl_xor_sync(~0u, v, 2)); }
__device__ __forceinline__ void mma16816(float (&d)[4], uint32_t a0, uint32_t a1, uint32_t a2, uint32_t a3, uint32_t b0, uint32_t b1) {
  asm("mma.sync.aligned.m16n8k16.row.col.f32.bf16.bf16.f32 {%0,%1,%2,%3}, {%4,%5,%6,%7}, {%8,%9}, {%0,%1,%2,%3};"
               : "+f"(d[0]), "+f"(d[1]), "+f"(d[2]), "+f"(d[3]) : "r"(a0), "r"(a1), "r"(a2), "r"(a3), "r"(b0), "r"(b1));
}
__device__ __forceinline__ uint32_t comp(const uint4& v, int i) { return i == 0 ? v.x : i == 1 ? v.y : i == 2 ? v.z : v.w; }
__device__ __forceinline__ void bulk_s2g(void* dst, uint32_t src, uint32_t bytes) {
  asm volatile("cp.async.bulk.global.shared::cta.bulk_group [%0], [%1], %2;\n" ::"l"(dst), "r"(src), "r"(bytes) : "memory");
}
__device__ __forceinline__ void bulk_red(void* dst, uint32_t src, uint32_t bytes) {
  asm volatile("cp.reduce.async.bulk.global.shared::cta.bulk_group.add.noftz.bf16 [%0], [%1], %2;\n" ::"l"(dst), "r"(src), "r"(bytes) : "memory");
}
#define BULK_COMMIT() asm volatile("cp.async.bulk.commit_group;\n" ::: "memory")
#define BULK_WAIT_READ() asm volatile("cp.async.bulk.wait_group.read 0;\n" ::: "memory")
#define BULK_WAIT() asm volatile("cp.async.bulk.wait_group 0;\n" ::: "memory")
__device__ __forceinline__ void cp16(uint32_t dst, const void* src) { asm volatile("cp.async.cg.shared.global [%0], [%1], 16;\n" ::"r"(dst), "l"(src) : "memory"); }
__device__ __forceinline__ void ldsm4(uint32_t (&r)[4], uint32_t p) {
  asm volatile("ldmatrix.sync.aligned.m8n8.x4.shared.b16 {%0,%1,%2,%3}, [%4];" : "=r"(r[0]), "=r"(r[1]), "=r"(r[2]), "=r"(r[3]) : "r"(p));
}
__device__ __forceinline__ void stsm4(uint32_t p, uint32_t a, uint32_t b, uint32_t c, uint32_t d) {
  asm volatile("stmatrix.sync.aligned.m8n8.x4.shared.b16 [%0], {%1,%2,%3,%4};" ::"r"(p), "r"(a), "r"(b), "r"(c), "r"(d) : "memory");
}
__device__ __forceinline__ uint32_t hfma2(uint32_t a, uint32_t b, uint32_t c) { uint32_t r; asm("fma.rn.bf16x2 %0, %1, %2, %3;" : "=r"(r) : "r"(a), "r"(b), "r"(c)); return r; }
__device__ __forceinline__ uint32_t hadd2(uint32_t a, uint32_t b) { uint32_t r; asm("add.rn.bf16x2 %0, %1, %2;" : "=r"(r) : "r"(a), "r"(b)); return r; }

__device__ __forceinline__ void product_load(const bool qk, const bool kperm, const __nv_bfloat16* __restrict__ L, const __nv_bfloat16* __restrict__ R,
                                             int d0, int c0, uint32_t sm) {
  const int ch = threadIdx.x & 31, w = threadIdx.x >> 5;
  const uint32_t smr = sm + 40 * 512;
  const __nv_bfloat16* lp = L + (d0 + (kperm ? ((w & 6) << 2) | (w & 1) : w)) * 256 + ch * 8;
  const uint32_t ls = sm + w * 512 + ((ch ^ w) << 4);
#pragma unroll
  for (int i = 0; i < 4; i++) cp16(ls + i * 4096, lp + i * (kperm ? 512 : 2048));
  cp16(ls + 4 * 4096, L + (248 + w) * 256 + ch * 8);
  if (qk) {
    const uint32_t rs = smr + (ch >> 3) * 1024 + w * 128 + (((ch ^ w) & 7) << 4);
#pragma unroll
    for (int i = 0; i < 4; i++) cp16(rs + i * 4096, R + (c0 + w + i * 8) * 256 + ch * 8);
    cp16(rs + 4 * 4096, R + (248 + w) * 256 + ch * 8);
  } else {
    const int e = w * 4 + (ch >> 3);
#pragma unroll
    for (int i = 0; i < 8; i++) cp16(smr + (e + i * 32) * 128 + (((ch ^ e) & 7) << 4), R + (e + i * 32) * 256 + c0 + (ch & 7) * 8);
  }
}
template <bool qk>
__device__ __forceinline__ void product_mma(uint8_t* img, int d0, int c0, uint32_t sm) {
  const int lane = threadIdx.x & 31, w = (threadIdx.x >> 5) & 3, l7 = lane & 7;
  const uint32_t pa = sm + (((lane & 8) ? 32 : w * 8) + l7) * 512;
  const uint32_t bd = mkdesc(sm + 40 * 512, 16);
  uint32_t a[16][4];
#pragma unroll
  for (int u = 0; u < 16; u++) ldsm4(a[u], pa + (u >> 2) * 128 + ((((u & 3) * 2 + (lane >> 4)) ^ l7) << 4));
  constexpr int NT = qk ? 4 : 8;
  float m[qk ? 20 : 32];
  pin(m);
  WG_FENCE();
#pragma unroll
  for (int u = 0; u < 16; u++) {
    if constexpr (qk) wgmma_rs40(m, a[u][0], a[u][1], a[u][2], a[u][3], bd + (u >> 2) * 64 + (u & 3) * 2, u);
    else wgmma_rs64t(m, a[u][0], a[u][1], a[u][2], a[u][3], bd + u * 128, u);
  }
  WG_COMMIT();
  WG_WAIT(0);
  pin(m);
  STAMPIF(threadIdx.x == 256, 27);
  float z = 0.f, u = 0.f;
  if constexpr (qk) { z = quad_sum(m[18] + m[19]); u = quad_sum(m[16] + m[17]); }
#pragma unroll
  for (int o = 4; o < 32; o *= 2) {
#pragma unroll
    for (int n = 0; n < NT; n++) { m[4 * n + 2] += __shfl_xor_sync(~0u, m[4 * n + 2], o); m[4 * n + 3] += __shfl_xor_sync(~0u, m[4 * n + 3], o); }
    if constexpr (qk) z += __shfl_xor_sync(~0u, z, o);
  }
  const int g = lane >> 2, t = lane & 3;
  u -= z * 0.125f;
  const float sc = d0 + w * 8 + g == 255 ? 0.f : qk ? 1.4426950408889634f / 16.f : 1.f;
  uint32_t v[NT];
#pragma unroll
  for (int n = 0; n < NT; n++) v[n] = pack2(fmaf(m[4 * n + 2] + u, -0.125f, m[4 * n]) * sc, fmaf(m[4 * n + 3] + u, -0.125f, m[4 * n + 1]) * sc);
  uint8_t* gp = img + ((d0 >> 3) + w) * 4096 + (c0 >> 6) * 1024 + g * 128;
  if constexpr (qk) {
    if (c0 == 224 && t == 3) v[3] &= 0xffffu;
    const uint32_t so = sm + 57344 + w * 1024;
    stsm4(so + l7 * 128 + (((lane >> 3) ^ l7) << 4), v[0], v[1], v[2], v[3]);
    __syncwarp();
    const uint4 r = lds128(so + g * 128 + ((t ^ g) << 4));
    stg128(gp + (((t + ((c0 >> 3) & 4)) ^ g) << 4), r.x, r.y, r.z, r.w);
  } else {
    stg128(gp + ((t ^ g) << 4), v[0], v[1], v[2], v[3]);
    stg128(gp + (((t + 4) ^ g) << 4), v[4], v[5], v[6], v[7]);
  }
}
__device__ __forceinline__ void product_done(unsigned* ctr) {
  STAMPIF(threadIdx.x == 256, 31);
  bar_sync(5, 128);
  if (threadIdx.x == (blockIdx.x < 64 ? 256 : 288)) garrive(ctr);
  STAMPIF(threadIdx.x == (blockIdx.x < 64 ? 256 : 288), 34);
  __syncwarp();
}

__global__ void __launch_bounds__(384, 1)
gps_kernel(const __nv_bfloat16* __restrict__ x, const int* __restrict__ src, const int* __restrict__ dst,
           const __nv_bfloat16* __restrict__ deg_inv, const __nv_bfloat16* __restrict__ w_msg,
           const __nv_bfloat16* __restrict__ wq, const __nv_bfloat16* __restrict__ wk, const __nv_bfloat16* __restrict__ wv,
           const __nv_bfloat16* __restrict__ w_out, __nv_bfloat16* __restrict__ out, Scratch* G) {
  extern __shared__ __align__(1024) uint8_t smem_raw[];
  const uint32_t sb = (uint32_t)__cvta_generic_to_shared(smem_raw);
  const uint32_t ring = sb + SM_RING, full0 = sb + SM_BAR, empty0 = full0 + 8 * NST, qbar0 = empty0 + 8 * NST;
  const uint32_t evt0 = qbar0 + 16, one0 = evt0 + 112;
  const uint32_t sfree = one0, wsent = one0 + 8, wfirst = one0 + 16, go = one0 + 24, bbar = one0 + 32, hread0 = one0 + 40, xbar0 = one0 + 56, cbar = one0 + 120, ebar = one0 + 128;
  const int wg = __shfl_sync(~0u, threadIdx.x >> 7, 0);
  const int lane = threadIdx.x & 31;
  const int cta = blockIdx.x;
  GSTAMPIF(threadIdx.x == 0, 0);
  const bool prod = cta < 126 || cta >= 130;
  const int pi = cta < 126 ? cta : cta - 4;
  const int kind = max((pi >> 5) - 1, 0), pd0 = ((pi >> (kind ? 2 : 3)) & 7) * 32, pc0 = kind ? (pi & 3) * 64 : (pi & 7) * 32;
  const bool early = cta > 125 && cta < 131;
  const int xfirst = cta == 130 ? 1 : early ? 4 : 0;
  const uint32_t cnt = sb + SM_META, box = sb + SM_AUX;
  const int e0 = cta * 1216, ne = min(E_ - e0, 1216);
  if (wg < 2) {
    if (prod) product_load(kind == 0, kind == 1, kind == 0 ? wq : kind == 1 ? w_msg : wv, kind == 0 ? wk : w_out, pd0, pc0, ring);
  } else if (threadIdx.x < 320) {
#pragma unroll 1
    for (int i = threadIdx.x - 256; i < 1024 + 32; i += 64) sts128(i < 1024 ? box + i * 16 : cnt + (i - 1024) * 16, 0, 0, 0, 0);
  } else if (threadIdx.x == 352) {
    cp16(sb + SM_BAR + 496, &G->epoch);
  } else if (threadIdx.x == 320) {
#pragma unroll
    for (int i = 0; i < 39; i++) mbar_init(full0 + 8 * i, i >= 3 && i < 6 ? 8 : i >= 8 && i < 22 ? 128 : i == 37 ? 384 : 1);
    asm volatile("fence.mbarrier_init.release.cluster;\n" ::: "memory");
    const int r = cta % 5, t0 = (cta / 5) * 3 + (r < 3 ? r : r - 2);
#pragma unroll 1
    for (int i = 0; i < xfirst; i++) {
      const int pc = r < 3 ? i : i ^ 4;
      mbar_expect_tx(xbar0 + 8 * i, 8192);
      bulk_g2s(sb + SM_Q + pc * 8192, x + (size_t)(t0 * 128 + pc * 16) * 256, 8192, xbar0 + 8 * i);
    }
  }
  STAMPIF(threadIdx.x == 128, 26);

  const int grp = cta / 5, role = cta < 130 ? cta - grp * 5 : (cta == 130 ? 1 : 5);
  const bool owner = role < 3;
  const int tA = grp * 3;
  int q0, n0, o0, q1 = 0, k1 = 0, n1 = 0, i1 = -1;
  if (cta >= 130) { q0 = 78; n0 = owner ? 64 : NKV - 64; o0 = 78; if (owner) i1 = 78; }
  else if (owner) { q0 = tA + role; n0 = role == 0 ? SCHED_A : role == 1 ? SCHED_B : SCHED_C; i1 = o0 = q0; }
  else if (role == 3) { q0 = tA + 1; n0 = SCHED_B1; o0 = NQT + grp; q1 = tA; k1 = SCHED_A; n1 = NKV - SCHED_A; }
  else { q0 = tA + 2; n0 = NKV - SCHED_C; o0 = q0; q1 = tA + 1; k1 = SCHED_B; n1 = NKV - SCHED_B - SCHED_B1; i1 = NQT + grp; }
  const int lu = (role == 3 ? tA : q0) * 2, lu2 = (tA + 1) * 2 + role - 3;

  const bool staged = role == 3;

  __syncthreads();
  asm volatile("cp.async.mbarrier.arrive.noinc.shared::cta.b64 [%0];\n" ::"r"(cbar) : "memory");

  if (wg == 2) {
    STAMPIF(threadIdx.x == 256, 40);
    mbar_wait(cbar, 0);
    if (prod) {
      PROXY_FENCE_SMEM();
      STAMPIF(threadIdx.x == 256, 24);
      if (kind == 0) product_mma<true>(G->w, pd0, pc0, ring); else product_mma<false>(G->w + kind * 131072, pd0, pc0, ring);
      product_done(&G->ctr[kind ? C_M : C_W]);
    }
    asm volatile("setmaxnreg.dec.sync.aligned.u32 56;\n");
    unsigned ep;
    asm volatile("ld.shared.u32 %0, [%1];" : "=r"(ep) : "r"(sb + SM_BAR + 496) : "memory");
    ep += 1;
    const int w = (threadIdx.x >> 5) & 3;
    if (w == 0) {
      if (lane == 0) {
        STAMPIF(true, 1);
        uint32_t st = 0, ph = 1;
        auto push = [&](const uint8_t* p, const uint8_t* rem) {
          mbar_wait(empty0 + 8 * st, ph);
          mbar_expect_tx(full0 + 8 * st, rem ? STB + 8192 : STB);
          bulk_g2s(ring + st * STB, p, STB, full0 + 8 * st);
          if (rem) bulk_g2s(sb + SM_REM, rem, 8192, full0 + 8 * st);
          if (++st == NST) { st = 0; ph ^= 1; }
        };
        auto qfill = [&](int e, int h, const uint8_t* p, const unsigned* flag, unsigned target, const float2* meta) {
          if (flag) gwait(flag, target);
          mbar_wait(evt0 + 16 * e + 8 * h, 0);
          PROXY_FENCE_SMEM();
          mbar_expect_tx(qbar0 + 8 * h, meta ? 32768 + 512 : 32768);
          bulk_g2s(sb + SM_Q + h * 32768, p + h * 32768, 32768, qbar0 + 8 * h);
          if (meta) bulk_g2s(sb + SM_META + h * 512, meta, 512, qbar0 + 8 * h);
        };
        auto lload = [&](int u, int blk, uint32_t dst) {
          const uint32_t lfull = xbar0 + 8 * u;
          const uint32_t nd = blk < 156 ? 128 : blk == 156 ? 32 : 0;
          mbar_expect_tx(lfull, 32768 + nd);
          bulk_g2s(dst, G->acc + (size_t)blk * 32768, 32768, lfull);
          if (nd) bulk_g2s(sb + SM_DINV + u * 128, deg_inv + blk * 64, nd, lfull);
        };
        gwait(&G->ctr[C_W], ep * CNT_W);
        PROXY_FENCE_SMEM();
        STAMPIF(true, 2);
        mbar_expect_tx(wfirst, 16384);
        bulk_g2s(ring, G->w, 16384, wfirst);
        mbar_expect_tx(full0, STB - 16384);
        bulk_g2s(ring + 16384, G->w + 16384, STB - 16384, full0);
        st = 1;
#pragma unroll 1
        for (int i = 1; i < 3; i++) push(G->w + i * STB, i == 2 ? G->w + 3 * STB : nullptr);
        mbar_arrive(wsent);
        gwait(&G->ctr[C_E], ep * CNT_E);
        STAMPIF(true, 3);
        const int ntot = n0 + n1;
        int h1 = 1;
#pragma unroll 1
        for (int j = 0; j < ntot + 3; j++) {
          if (j == (owner ? 2 : 1)) gwait(&G->ctr[C_F], ep * CNT_F);
          if (j == 3) gwait(&G->ctr[C_H], ep * CNT_H);
          if (j == ntot) {
            gwait(&G->ctr[C_G], ep * CNT_G);
            PROXY_FENCE_SMEM();
            if (role == 4) lload(0, lu, sb + SM_AUX);
            if (role == 3) lload(2, lu2, sb + SM_AUX);
          }
          int kt = j >= n0 ? k1 + j - n0 : owner ? j : NKV - 1 - j;
          if (kt < 3) kt = kt == 2 ? 21 : 123 - kt; else if (kt >= 21 && kt < 24) kt -= 21; else if (kt == 122 || kt == 123) kt -= 100;
          const uint8_t* wp_ = G->w + (owner ? 262144 : 131072) + (j - ntot) * STB;
          push(j < ntot ? G->ht + (size_t)kt * STB : wp_, j == ntot ? wp_ + 3 * STB : nullptr);
          if (j == JBG) { mbar_arrive(qbar0); mbar_arrive(qbar0 + 8); }
          if (j == JSCAT) mbar_arrive(go);
          if (n1) {
            const int h = j - n0;
            if (h == 0 || h == 1) qfill(1, h, G->qt + (size_t)q1 * 65536, h ? nullptr : &G->ctr[C_M], ep * CNT_M, nullptr);
          }
          const int h = j - ntot;
          if (h == 1 && owner) {
            unsigned v, fr;
            do {
              asm volatile("{\n.reg .pred p;\nmbarrier.test_wait.parity.shared::cta.b64 p, [%1], %2;\nselp.u32 %0, 1, 0, p;\n}\n" : "=r"(fr) : "r"(empty0 + 8 * st), "r"(ph) : "memory");
              asm volatile("ld.acquire.gpu.global.u32 %0, [%1];" : "=r"(v) : "l"(&G->pflag[i1 * 2 + 1]) : "memory");
            } while (v != ep && !fr);
            if (v != ep) h1 = 2;
          }
          if ((h == 0 || h == h1) && i1 >= 0)
            qfill(n1 ? 6 : 1, h != 0, G->part + (size_t)i1 * 65536, h == 1 && owner ? nullptr : &G->pflag[i1 * 2 + (h != 0)], ep, &G->meta[i1 * 128 + (h != 0) * 64]);
          if ((h == 0 || h == 1) && i1 < 0) { mbar_wait(evt0 + (n1 ? 96 : 16) + 8 * h, 0); lload(h, lu + h, sb + SM_Q + h * 32768); }
        }
        if (role == 4) {
          mbar_wait(evt0 + 80, 0); PROXY_FENCE_SMEM(); mbar_wait(wsent, 1); lload(1, lu + 1, sb + SM_AUX);
          mbar_wait(evt0 + 88, 0); PROXY_FENCE_SMEM(); mbar_wait(wfirst, 1); lload(2, lu2, sb + SM_AUX);
        }
        if (cta == 0) G->epoch = ep;
      }
    } else {
      if (w == 3 && lane == 0) {
        const int pub = role == 0 ? 3 : owner ? 1 : 2;
        if (!early) mbar_wait(wsent, 0);
#pragma unroll 1
        for (int h = 0; h < 2; h++) {
          if (pub >> h & 1) { mbar_wait(evt0 + 64 + 8 * h, 0); bulk_s2g(G->ht + (size_t)q0 * 65536 + h * 32768, sb + SM_Q + h * 32768, cta >= 130 ? 8192 : pub == 3 && h ? 32768 - HSPLIT : 32768); }
          BULK_COMMIT();
        }
        asm volatile("cp.async.bulk.wait_group 1;\n" ::: "memory");
        mbar_arrive(hread0);
        if (pub == 3 && HSPLIT) {
          mbar_wait(empty0, 0);
          __nanosleep(50);
          bulk_s2g(G->ht + (size_t)q0 * 65536 + 65536 - HSPLIT, sb + SM_Q + 65536 - HSPLIT, HSPLIT);
          BULK_COMMIT();
        }
        BULK_WAIT();
        mbar_arrive(hread0 + 8);
        GPU_FENCE();
        if (early) garrive_relaxed(&G->ctr[C_E]);
        if (cta > 20 && cta < 25) garrive_relaxed(&G->ctr[C_F]);
        garrive_relaxed(&G->ctr[C_H]);
        STAMPIF(true, 30);
      }
      __syncwarp();
      mbar_wait(qbar0 + 8, 0);
      if (w < 3) {
        const uint32_t eb = box + 16384;
        if (threadIdx.x == 288) {
          mbar_expect_tx(ebar, ne * 8);
          bulk_g2s(eb, src + e0, ne * 4, ebar);
          bulk_g2s(eb + 8192, dst + e0, ne * 4, ebar);
        }
        __syncwarp();
        mbar_wait(ebar, 0);
#pragma unroll 1
        for (int i = threadIdx.x - 288; i < ne / 4; i += 64) {
          const uint4 vs = lds128(eb + i * 16), vd = lds128(eb + 8192 + i * 16);
          uint32_t tl[4], sl[4];
#pragma unroll
          for (int u = 0; u < 4; u++) {
            tl[u] = comp(vs, u) / BN;
            asm volatile("atom.shared.add.u32 %0, [%1], 1;" : "=r"(sl[u]) : "r"(cnt + tl[u] * 4) : "memory");
          }
#pragma unroll
          for (int u = 0; u < 4; u++)
            if (sl[u] < 32) asm volatile("st.shared.u32 [%0], %1;" ::"r"(box + tl[u] * 128 + sl[u] * 4), "r"(0x80000000u | (comp(vs, u) - tl[u] * BN) << 14 | comp(vd, u)) : "memory");
          if ((sl[0] | sl[1] | sl[2] | sl[3]) >= 32) {
#pragma unroll 1
            for (int u = 0; u < 4; u++) {
              const uint32_t a = u & 1 ? (u & 2 ? sl[3] : sl[1]) : (u & 2 ? sl[2] : sl[0]);
              if (a >= 32) {
                uint32_t k;
                asm volatile("atom.shared.add.u32 %0, [%1], 1;" : "=r"(k) : "r"(cnt + NKV * 4) : "memory");
                G->ovf[cta * 1280 + k] = comp(vs, u) << 14 | comp(vd, u);
              }
            }
          }
        }
        PROXY_FENCE_SMEM();
        STAMPIF(threadIdx.x == 288, 36);
        bar_arrive(8, 96);
      }
      if (w == 3) {
#pragma unroll 4
        for (int i = 0; i < 16; i++) sts128(sb + SM_REM + i * 512 + lane * 16, 0, 0, 0, 0);
        PROXY_FENCE_SMEM();
        bar_sync(8, 96);
        if (lane == 0) {
#pragma unroll 1
          for (int i = 0; i < 5; i++) {
            const size_t off = (size_t)cta * 40960 + i * 8192;
            if (cta < NKV) { mbar_expect_tx(bbar, 8192); bulk_g2s(box + 16384, (const uint8_t*)x + off, 8192, bbar); }
            bulk_s2g(G->acc + off, sb + SM_REM, 8192);
            if (cta < NKV) { mbar_wait(bbar, i & 1); bulk_s2g((uint8_t*)out + off, box + 16384, 8192); }
            BULK_COMMIT();
            BULK_WAIT();
          }
          if (cta < 130 && role < 2) {
            mbar_wait(evt0, 0);
            mbar_wait(evt0 + 8, 0);
#pragma unroll 1
            for (int i = 0; i < 8; i++) {
              bulk_s2g(G->qt + (size_t)q0 * 65536 + i * 8192, sb + SM_Q + i * 8192, 8192);
              BULK_COMMIT();
              BULK_WAIT();
            }
          }
        }
        __syncwarp();
        bar_arrive(6, 96);
        if (lane == 0 && !owner) {
#pragma unroll 1
          for (int u = n1 ? 0 : 2; u < 4; u++) {
            mbar_wait(evt0 + 32 + 8 * u, 0);
            if (staged && u == 0) {
              mbar_wait(evt0 + 40, 0);
#pragma unroll 1
              for (int i = 0; i < 10; i++) {
                bulk_s2g(G->part + (size_t)o0 * 65536 + (i < 5 ? i * 4096 : 12288 + i * 4096), sb + SM_REM + i * 4096, 4096);
                BULK_COMMIT();
                BULK_WAIT();
              }
              mbar_arrive(sfree);
            }
            gset(&G->pflag[(u < 2 || !n1 ? o0 : q1) * 2 + (u & 1)], ep);
            if (u >= 2) mbar_arrive(u == 2 ? wsent : wfirst);
          }
        }
      } else {
        bar_sync(6, 96);
        int novf;
        asm volatile("ld.shared.u32 %0, [%1];" : "=r"(novf) : "r"(cnt + NKV * 4) : "memory");
        if (threadIdx.x == 288) {
          bulk_s2g(G->box + cta * NKV * 32, box, NKV * 128);
          BULK_COMMIT();
          BULK_WAIT();
          garrive(&G->ctr[C_M]);
          STAMPIF(true, 43);
          gwait(&G->ctr[C_H], ep * CNT_H);
          if (staged) mbar_wait(sfree, 0);
          if (cta < NKV) { mbar_expect_tx(bbar, STB); bulk_g2s(sb + SM_REM, G->ht + (size_t)cta * STB, STB, bbar); }
        }
        __syncwarp();
        if (cta < NKV) {
          mbar_wait(bbar, 1);
#pragma unroll 1
          for (int gi = 0; gi < 10; gi++) {
            uint4 v[4];
#pragma unroll
            for (int u = 0; u < 4; u++) { const int rr = (w - 1) * 4 + u; v[u] = lds128(sb + SM_REM + gi * 4096 + (lane >> 3) * 1024 + rr * 128 + (((lane ^ rr) & 7) << 4)); }
            bar_sync(5, 64);
#pragma unroll
            for (int u = 0; u < 4; u++) sts128(sb + SM_REM + gi * 4096 + ((w - 1) * 4 + u) * 512 + lane * 16, v[u].x, v[u].y, v[u].z, v[u].w);
          }
          PROXY_FENCE_SMEM();
          bar_sync(5, 64);
        }
        STAMPIF(threadIdx.x == 288, 44);
        mbar_wait(go, 0);
        if (lane == 0) gwait(&G->ctr[C_M], ep * CNT_M);
        __syncwarp();
        STAMPIF(threadIdx.x == 288, 4);
        if (cta < NKV) {
          const unsigned* bp = G->box + ((w - 1) * NKV + cta) * 32 + lane;
          unsigned e = __ldcg(bp);
#pragma unroll 1
          for (int i = 0; i < NCTA / 2; i++) {
            bp += 2 * NKV * 32;
            unsigned en = 0;
            if (i + 1 < NCTA / 2) en = __ldcg(bp);
            if (e) bulk_red(G->acc + (size_t)(e & 0x3fff) * 512, sb + SM_REM + ((e >> 14) & 127) * 512, 512);
            BULK_COMMIT();
            BULK_WAIT_READ();
            e = en;
          }
        }
#pragma unroll 1
        for (int i = w - 1; i < novf; i += 2) {
          const int e = __ldcg(&G->ovf[cta * 1280 + i]), r = e >> 14;
          const uint4 v = ldg_cg(G->ht + (size_t)(r >> 3) * 4096 + (lane >> 3) * 1024 + (r & 7) * 128 + (((lane ^ r) & 7) << 4));
          asm volatile("red.global.add.noftz.v4.bf16x2 [%0], {%1,%2,%3,%4};" ::"l"(G->acc + (size_t)(e & 0x3fff) * 512 + lane * 16), "r"(v.x), "r"(v.y), "r"(v.z), "r"(v.w) : "memory");
        }
        BULK_WAIT();
        __syncwarp();
        if (lane == 0) garrive(&G->ctr[C_G]);
        STAMPIF(threadIdx.x == 288, 5);
      }
    }
  } else {
    const int g = lane >> 2, t = lane & 3, wp = __shfl_sync(~0u, (threadIdx.x >> 5) & 3, 0), tid = threadIdx.x & 127;
    const uint32_t qh = sb + SM_Q + wg * 32768;
    const uint32_t qw = qh + wp * 8192;
    const uint32_t qbar = qbar0 + 8 * wg;
    auto event = [&](int e) { mbar_arrive(evt0 + 16 * e + 8 * wg); };
    if (wg == 1) bar_arrive(1, 256);
    {
      const int xr0 = min(q0 * 128 + wg * 64 + wp * 16, N_ - 16), xord = (owner || !early ? wg : wg ^ 1) * 4 + wp;
      if (cta >= 64 && xord >= 4) mbar_wait(xbar0 + 8 * (xord - 4), 0);
      if (lane == 0 && xord >= xfirst) {
        mbar_expect_tx(xbar0 + 8 * xord, 8192);
        bulk_g2s(qw, x + (size_t)xr0 * 256, 8192, xbar0 + 8 * xord);
      }
      STAMPIF(threadIdx.x == 0, 35);
      mbar_wait(xbar0 + 8 * xord, 0);
      STAMPIF(threadIdx.x == 0, 25);
      STAMPIF(threadIdx.x == 224, 41);
      uint4 xa[8], xb[8];
      const uint32_t sw = (g & 1) << 6;
#pragma unroll
      for (int J = 0; J < 8; J++) xa[J] = lds128(qw + g * 512 + t * 16 + ((J * 64) ^ sw));
#pragma unroll
      for (int J = 0; J < 8; J++) xb[J] = lds128(qw + 4096 + g * 512 + t * 16 + ((J * 64) ^ sw));
      __syncwarp();
      const uint32_t wa = qw + g * 128 + (((t ^ g) << 4) ^ sw);
#pragma unroll
      for (int rr = 0; rr < 2; rr++) {
        float sm[2][4] = {}, f[64], q[4] = {};
#pragma unroll
        for (int J = 0; J < 8; J++) {
          const uint4 v = rr ? xb[J] : xa[J];
          mma16816(sm[J & 1], v.x, v.y, v.z, v.w, 0x3f803f80u, 0x3f803f80u);
#pragma unroll
          for (int i = 0; i < 4; i++) {
            f[J * 8 + 2 * i] = blo(comp(v, i)); f[J * 8 + 2 * i + 1] = bhi(comp(v, i));
            q[i] = fmaf(f[J * 8 + 2 * i], f[J * 8 + 2 * i], q[i]); q[i ^ 2] = fmaf(f[J * 8 + 2 * i + 1], f[J * 8 + 2 * i + 1], q[i ^ 2]);
          }
        }
        const float mean = ((sm[0][0] + sm[0][2]) + (sm[1][0] + sm[1][2])) * (1.f / 256.f);
        const float rstd = rsq(fmaxf(fmaf(-mean, mean, quad_sum((q[0] + q[1]) + (q[2] + q[3])) * (1.f / 256.f)), 0.f) + 1e-5f);
#pragma unroll
        for (int J = 0; J < 8; J++) {
          const bool lastc = J >= 6 && (lane & 7) == (J == 7 ? 3 : 7);
          const float c = (lastc ? f[J * 8 + 7] : mean) * -rstd;
          uint32_t r3 = pack2(fmaf(f[J * 8 + 6], rstd, c), fmaf(f[J * 8 + 7], rstd, c));
          if (lastc) r3 = (r3 & 0xffffu) | 0x3f800000u;
          sts128((wa ^ ((J & 1) << 6)) + rr * 4096 + (J >> 1) * 1024, pack2(fmaf(f[J * 8], rstd, c), fmaf(f[J * 8 + 1], rstd, c)),
                 pack2(fmaf(f[J * 8 + 2], rstd, c), fmaf(f[J * 8 + 3], rstd, c)), pack2(fmaf(f[J * 8 + 4], rstd, c), fmaf(f[J * 8 + 5], rstd, c)), r3);
        }
      }
      STAMPIF(threadIdx.x == 0, 38);
      PROXY_FENCE_SMEM();
      STAMPIF(threadIdx.x == 0, 39);
    }
    event(4);
    bar_sync(3 + wg, 128);
    STAMPIF(tid == 0, wg ? 42 : 6);
    asm volatile("setmaxnreg.inc.sync.aligned.u32 224;\n");

    float o[128];
    uint32_t ga[64], qr[NQR * 4];
    uint32_t st = 0, ph = 0, pst = 0;
    const uint32_t qd = mkdesc(qh, 16), kd0 = mkdesc(ring, 16), vd0 = mkdesc(ring, 1024), rd = mkdesc(sb + SM_REM, 1024);
    auto wait_full = [&]() { mbar_wait(full0 + 8 * st, ph); };
    auto advance = [&]() { pst = st; if (++st == NST) { st = 0; ph ^= 1; } };
    auto release = [&]() { if (lane == 0) mbar_arrive(empty0 + 8 * pst); };

    {
      mbar_wait(wfirst, 0);
      bar_sync(1 + wg, 256);
      STAMPIF(threadIdx.x == 0, 28);
      WG_FENCE();
      wgmma_ss256(o, qd, vd0, 0);
      wgmma_ss256(o, qd + 2, vd0 + 512, 1);
#pragma unroll
      for (int c = 0; c < 3; c++) {
        wait_full();
        WG_FENCE();
#pragma unroll
        for (int k = c ? 0 : 2; k < 5; k++) {
          const int ks = c * 5 + k;
          wgmma_ss256(o, qd + (ks >> 2) * 64 + (ks & 3) * 2, vd0 + c * (STB >> 4) + k * 512, 1);
          if (c > 0 && k == EREL) { WG_COMMIT(); WG_WAIT(1); release(); }
        }
        if (c == 2) wgmma_ss256(o, qd + 3 * 64 + 6, rd, 1);
        WG_COMMIT();
        if (c == 2) bar_arrive(2 - wg, 256);
        advance();
      }
      WG_WAIT(0);
      pin(o);
      release();
      STAMPIF(threadIdx.x == 0, 29);
      mbar_wait(hread0 + 8 * wg, 0);
      bar_sync(3 + wg, 128);
      STAMPIF(threadIdx.x == 0, 45);
      const uint32_t sa = qw + ((lane >> 3) & 1) * 4096 + (lane & 7) * 128 + (((lane >> 4) ^ (lane & 7)) << 4);
#pragma unroll
      for (int i = 0; i < 32; i += 2)
        stsm4((sa ^ ((i & 7) << 4)) + (i >> 3) * 1024, pack2(o[4 * i], o[4 * i + 1]), pack2(o[4 * i + 2], o[4 * i + 3]), pack2(o[4 * i + 4], o[4 * i + 5]), pack2(o[4 * i + 6], o[4 * i + 7]));
#pragma unroll
      for (int i = 0; i < NQR * 4; i++) qr[i] = pack2(o[128 - NQR * 8 + 2 * i], o[129 - NQR * 8 + 2 * i]);
      STAMPIF(threadIdx.x == 0, 46);
      PROXY_FENCE_SMEM();
      event(0);
    }
    STAMPIF(threadIdx.x == 0, 7);

    float s[BN / 2];
    uint32_t p[BN / 4];
    float m0, m1, mb0, mb1, l0, l1;
    auto qk = [&]() {
#pragma unroll
      for (int ks = 0; ks < 16; ks++) {
        const uint32_t off = (ks >> 2) * 64 + (ks & 3) * 2;
        const int r = (ks - 16 + NQR) * 4;
        const uint64_t q64 = (uint64_t)DESC_HI << 32 | qd, k64 = ((uint64_t)DESC_HI << 32 | kd0) + st * (STB >> 4);
        if (r < 0) wgmma_qk64(s, q64 + off, k64 + off, ks > 0);
        else wgmma_qkr64(s, qr[r], qr[r + 1], qr[r + 2], qr[r + 3], k64 + off, 1);
      }
      WG_COMMIT();
    };
    auto pv = [&](int keep) {
#pragma unroll
      for (int ks = 0; ks < BN / 16; ks++) wgmma_pv64(o, p[ks * 4], p[ks * 4 + 1], p[ks * 4 + 2], p[ks * 4 + 3], ((uint64_t)DESC_HI << 32 | vd0) + pst * (STB >> 4) + ks * 512, ks ? 1 : keep);
      WG_COMMIT();
    };
    auto softmax_slow = [&](bool dump, bool first) {
      const float om0 = m0, om1 = m1;
      if (dump) {
        m0 = m1 = -INFINITY;
        mb0 = mb1 = 0.f;
        if (staged) {
#pragma unroll
          for (int k = 0; k < 10; k++)
            sts128(sb + SM_REM + wg * 20480 + k * 2048 + tid * 16, pack2(o[8 * k], o[8 * k + 1]), pack2(o[8 * k + 2], o[8 * k + 3]), pack2(o[8 * k + 4], o[8 * k + 5]), pack2(o[8 * k + 6], o[8 * k + 7]));
          PROXY_FENCE_SMEM();
        }
      }
      float x0 = fmaxf(s[0], s[1]), x1 = fmaxf(s[2], s[3]);
#pragma unroll
      for (int i = 1; i < BN / 8; i++) { x0 = fmaxf(x0, fmaxf(s[4 * i], s[4 * i + 1])); x1 = fmaxf(x1, fmaxf(s[4 * i + 2], s[4 * i + 3])); }
      x0 = quad_max(x0) + mb0; x1 = quad_max(x1) + mb1;
      float r0 = x0 < m0 ? m0 : ceilf(x0 + 32.f), r1 = x1 < m1 ? m1 : ceilf(x1 + 32.f);
      uint32_t pk = pack2(r0, r1);
      const float b0 = blo(pk), b1 = bhi(pk);
      const bool ok0 = fabsf(b0 - r0) <= 8.f, ok1 = fabsf(b1 - r1) <= 8.f;
      if (ok0) r0 = b0;
      if (ok1) r1 = b1;
      const float a0 = ex2(m0 - r0), a1 = ex2(m1 - r1), d0 = r0 - mb0, d1 = r1 - mb1;
      m0 = r0; m1 = r1;
      mb0 = b0; mb1 = b1;
      if (t == 3) {
        pk ^= 0x80008000u;
        qr[NQR * 4 - 2] = __byte_perm(qr[NQR * 4 - 2], pk, 0x5410);
        qr[NQR * 4 - 1] = __byte_perm(qr[NQR * 4 - 1], pk, 0x7610);
      }
      if (dump) {
        if (t == 3) {
          G->meta[o0 * 128 + wg * 64 + wp * 16 + g] = make_float2(om0, o[125]);
          G->meta[o0 * 128 + wg * 64 + wp * 16 + g + 8] = make_float2(om1, o[127]);
        }
        uint8_t* pp = G->part + (size_t)o0 * 65536 + wg * 32768 + tid * 16;
#pragma unroll
        for (int k = 15; k >= 0; k--) {
          if (k == 9 && staged) break;
          stg128(pp + k * 2048, pack2(o[8 * k], o[8 * k + 1]), pack2(o[8 * k + 2], o[8 * k + 3]), pack2(o[8 * k + 4], o[8 * k + 5]), pack2(o[8 * k + 6], o[8 * k + 7]));
        }
        event(2);
        STAMPIF(tid == 0, 14 + wg);
      }
      if (!first && __any_sync(~0u, a0 != 1.f || a1 != 1.f)) {
#pragma unroll
        for (int i = 0; i < 32; i++) { o[4 * i] *= a0; o[4 * i + 1] *= a0; o[4 * i + 2] *= a1; o[4 * i + 3] *= a1; }
      }
#pragma unroll
      for (int i = 0; i < BN / 8; i++) {
        p[2 * i] = pack2(ex2(s[4 * i] - d0), ex2(s[4 * i + 1] - d0));
        p[2 * i + 1] = pack2(ex2(s[4 * i + 2] - d1), ex2(s[4 * i + 3] - d1));
      }
      return (bool)__any_sync(~0u, !(ok0 && ok1));
    };
    {
      int left = n0 + n1 - 1;
      wait_full();
      bar_sync(1 + wg, 256);
      WG_FENCE();
      qk();
      bar_arrive(2 - wg, 256);
      m0 = m1 = -INFINITY;
      mb0 = mb1 = 0.f;
      WG_WAIT(0);
      pin(s);
      GSTAMPIF(threadIdx.x == 0, 8);
      STAMPIF(threadIdx.x == 128, 53);
      bool slow = softmax_slow(false, true);
      STAMPIF(tid == 0, 32 + wg);
      int keep = 0;
      advance();
#pragma unroll 1
      do {
        const bool sw = left == n1;
        wait_full();
        bar_sync(1 + wg, 256);
        WG_FENCE();
        pv(keep);
        keep = !sw;
        if (sw) {
          mbar_wait(qbar, 1);
          slow = true;
#pragma unroll
          for (int i = 0; i < NQR; i++) {
            const int ks = 16 - NQR + i;
            uint32_t f[4];
            ldsm4(f, qw + ((lane >> 3) & 1) * 4096 + (ks >> 2) * 1024 + (lane & 7) * 128 + ((((ks & 3) * 2 + (lane >> 4)) ^ (lane & 7)) << 4));
            qr[4 * i] = f[0]; qr[4 * i + 1] = f[1]; qr[4 * i + 2] = f[2]; qr[4 * i + 3] = f[3];
          }
        }
        WG_FENCE();
        qk();
        bar_arrive(2 - wg, 256);
        WG_WAIT(1);
        release();
        WG_WAIT(0);
        pin(s); pin(o);
        left--;
        if (left == n1 || left == 0) event(left == n1 ? 1 : 6);
        if (!slow) {
          uint32_t acc = 0;
#pragma unroll
          for (int i = 0; i < BN / 4; i++) { p[i] = pack2(ex2(s[2 * i]), ex2(s[2 * i + 1])); acc |= p[i]; }
          slow = __any_sync(~0u, (acc & 0x40004000u) != 0);
        }
        if (slow) {
          GSTAMPIF(threadIdx.x == 0 && sw, 9);
          slow = softmax_slow(sw, sw);
        }
        advance();
      } while (left);
      bar_sync(1 + wg, 256);
      WG_FENCE();
      pv(1);
      bar_arrive(2 - wg, 256);
      WG_WAIT(0);
      pin(o);
      release();
      GSTAMPIF(tid == 0, 10 + wg);
      if (i1 >= 0) {
        mbar_wait(qbar, n1 ? 0 : 1);
        STAMPIF(tid == 0, 18 + wg);
        const uint32_t ma = sb + SM_META + wg * 512 + (wp * 16 + g) * 8;
        float2 h0, h1;
        asm volatile("ld.shared.v2.f32 {%0,%1}, [%2];" : "=f"(h0.x), "=f"(h0.y) : "r"(ma) : "memory");
        asm volatile("ld.shared.v2.f32 {%0,%1}, [%2];" : "=f"(h1.x), "=f"(h1.y) : "r"(ma + 64) : "memory");
#pragma unroll
        for (int k = 0; k < 16; k++) { const uint4 v = lds128(qh + k * 2048 + tid * 16); ga[4 * k] = v.x; ga[4 * k + 1] = v.y; ga[4 * k + 2] = v.z; ga[4 * k + 3] = v.w; }
        if (__any_sync(~0u, h0.x - m0 > 20.f || h1.x - m1 > 20.f)) {
          const float t0 = fmaxf(m0, h0.x), t1 = fmaxf(m1, h1.x), a0 = ex2(m0 - t0), a1 = ex2(m1 - t1);
          m0 = t0; m1 = t1;
#pragma unroll
          for (int i = 0; i < 32; i++) { o[4 * i] *= a0; o[4 * i + 1] *= a0; o[4 * i + 2] *= a1; o[4 * i + 3] *= a1; }
        }
        const float b0 = ex2(h0.x - m0), b1 = ex2(h1.x - m1);
        l0 = fmaf(b0, h0.y, o[125]); l1 = fmaf(b1, h1.y, o[127]);
        const uint32_t bb0 = pack2(b0, b0), bb1 = pack2(b1, b1);
#pragma unroll
        for (int i = 0; i < 64; i++) ga[i] = hfma2(ga[i], (i & 1) ? bb1 : bb0, pack2(o[2 * i], o[2 * i + 1]));
      } else {
        l0 = o[125]; l1 = o[127];
#pragma unroll
        for (int i = 0; i < 64; i++) ga[i] = pack2(o[2 * i], o[2 * i + 1]);
      }
      if (!owner) {
        if (wg) mbar_wait(wsent, 1);
        const int slot = n1 ? q1 : o0;
        uint8_t* pp = G->part + (size_t)slot * 65536 + wg * 32768 + tid * 16;
#pragma unroll
        for (int k = 0; k < 16; k++) stg128(pp + k * 2048, ga[4 * k], ga[4 * k + 1], ga[4 * k + 2], ga[4 * k + 3]);
        if (t == 3) {
          G->meta[slot * 128 + wg * 64 + wp * 16 + g] = make_float2(m0, l0);
          G->meta[slot * 128 + wg * 64 + wp * 16 + g + 8] = make_float2(m1, l1);
        }
        event(3);
        STAMPIF(tid == 0, 16 + wg);
      }
    }

    float f0 = rcp(__shfl_sync(~0u, l0, lane | 3)), f1 = rcp(__shfl_sync(~0u, l1, lane | 3));
#pragma unroll 1
    for (int rnd = 0;; rnd++) {
      int r0 = q0 * 128 + wg * 64;
      if (!owner) {
        r0 = (rnd ? lu2 : lu + wg) * 64;
        mbar_wait(xbar0 + 8 * (rnd * 2 + wg), 1);
        const uint32_t la = (rnd || role == 4 ? sb + SM_AUX + wp * 8192 : qw) + g * 512 + t * 16;
#pragma unroll
        for (int J = 0; J < 8; J++) {
          const uint4 va = lds128(la + J * 64), vb = lds128(la + 4096 + J * 64);
          ga[8 * J] = va.x; ga[8 * J + 1] = vb.x; ga[8 * J + 2] = va.y; ga[8 * J + 3] = vb.y;
          ga[8 * J + 4] = va.z; ga[8 * J + 5] = vb.z; ga[8 * J + 6] = va.w; ga[8 * J + 7] = vb.w;
        }
        uint32_t d0, d1;
        asm volatile("ld.shared.u16 %0, [%1];" : "=r"(d0) : "r"(sb + SM_DINV + (rnd * 128 + wg * 64 + wp * 16 + g) * 2) : "memory");
        asm volatile("ld.shared.u16 %0, [%1];" : "=r"(d1) : "r"(sb + SM_DINV + (rnd * 128 + wg * 64 + wp * 16 + g + 8) * 2) : "memory");
        f0 = blo(d0); f1 = blo(d1);
        if (rnd == 0) event(5);
      }
      r0 += wp * 16;
#pragma unroll
      for (int i = 0; i < 64; i++) asm volatile("" : "+r"(ga[i])::"memory");
      STAMPIF(tid == 0, 47 + wg);
      bar_sync(1 + wg, 256);
#pragma unroll
      for (int c = 0; c < 3; c++) {
        if (rnd == 0) wait_full();
        WG_FENCE();
        const uint32_t wd = vd0 + st * (STB >> 4);
#pragma unroll
        for (int k = 0; k < 5; k++) { const int ks = c * 5 + k; wgmma_rs256(o, ga[ks * 4], ga[ks * 4 + 1], ga[ks * 4 + 2], ga[ks * 4 + 3], wd + k * 512, ks != 0); }
        if (c == 2) wgmma_rs256(o, ga[60], ga[61], ga[62], ga[63], rd, 1);
        WG_COMMIT();
        advance();
      }
      if (wg == 0 ? rnd == 0 : n1 != 0) bar_arrive(2 - wg, 256);
      BULK_WAIT_READ();
      __syncwarp();
      WG_WAIT(0);
      pin(o);
      STAMPIF(tid == 0, 20 + wg);
      const uint32_t ap = qw + g * 512 + t * 16 + ((g & 1) << 6);
      const bool odd = g & 1;
#pragma unroll
      for (int h = 0; h < 2; h++) {
        const float f = h ? f1 : f0;
#pragma unroll
        for (int J = 0; J < 8; J += 2) {
          uint32_t y[8];
#pragma unroll
          for (int i = 0; i < 8; i++) y[i] = pack2(o[16 * J + 4 * i + 2 * h] * f, o[16 * J + 4 * i + 2 * h + 1] * f);
          sts128(ap + h * 4096 + J * 64, odd ? y[4] : y[0], odd ? y[5] : y[1], odd ? y[6] : y[2], odd ? y[7] : y[3]);
          sts128((ap ^ 64) + h * 4096 + J * 64, odd ? y[0] : y[4], odd ? y[1] : y[5], odd ? y[2] : y[6], odd ? y[3] : y[7]);
        }
        PROXY_FENCE_SMEM();
        __syncwarp();
        if (lane == 0 && r0 < N_) { bulk_red((uint8_t*)out + (size_t)r0 * 512 + h * 4096, qw + h * 4096, 4096); BULK_COMMIT(); }
      }
      STAMPIF(tid == 0, 51 + wg);
      if (rnd || wg || !n1) break;
    }
    BULK_WAIT_READ();
    GSTAMPIF(tid == 0, 22 + wg);
    PROF_DUMP();
  }
}

}

extern "C" void kernel_launch(void* const* d_in, const int* in_sizes, int n_in, void* d_out, int out_size) {
  (void)in_sizes; (void)n_in; (void)out_size;
  void* scratch = nullptr;
  cudaGetSymbolAddress(&scratch, g_scratch);
  cudaFuncSetAttribute(gps_kernel, cudaFuncAttributeMaxDynamicSharedMemorySize, SM_TOTAL);
  gps_kernel<<<NCTA, 384, SM_TOTAL>>>((const __nv_bfloat16*)d_in[0], (const int*)d_in[1], (const int*)d_in[2],
                                      (const __nv_bfloat16*)d_in[3], (const __nv_bfloat16*)d_in[4], (const __nv_bfloat16*)d_in[5],
                                      (const __nv_bfloat16*)d_in[6], (const __nv_bfloat16*)d_in[7], (const __nv_bfloat16*)d_in[8],
                                      (__nv_bfloat16*)d_out, (Scratch*)scratch);
}
```

```cpp
#include <cuda_runtime.h>
#include <cuda_bf16.h>
#include <stdint.h>

namespace {

constexpr int N_ = 10000, E_ = 160000, NQT = 79, NPAD = NQT * 128;
constexpr int BN = 80, NKV = 125, NST = 3, STB = BN * 512, NCTA = 132;
constexpr int NSLOT = NQT + 26;
#define SCHED_A 76
#define SCHED_B 76
#define SCHED_C 76
#define SCHED_B1 25
#define NQR 1
#define EREL 0
#define HSPLIT 16384
#define JBG 5
#define JSCAT 45
constexpr int SM_Q = 0, SM_RING = 65536, SM_REM = SM_RING + NST * STB, SM_AUX = SM_REM + 8192, SM_META = SM_AUX + 32768;
constexpr int SM_BAR = SM_META + 1024, SM_DINV = SM_BAR + 1280, SM_TOTAL = SM_BAR + 1792;
constexpr unsigned CNT_W = 64, CNT_H = NCTA, CNT_E = 5, CNT_F = 4, CNT_M = NCTA + 64, CNT_G = NCTA * 2;
constexpr int C_W = 0, C_H = 32, C_E = 64, C_M = 96, C_G = 128, C_F = 160;

struct Scratch {
  unsigned ctr[6 * 32], epoch, pad0[31], pflag[NSLOT * 2], pad1[1024 - 7 * 32 - NSLOT * 2];
  uint8_t w[3 * 131072];
  float2 meta[NSLOT * 128];
  uint8_t ht[NPAD * 512];
  uint8_t qt[NPAD * 512];
  uint8_t acc[NCTA * 40960];
  uint8_t part[NSLOT * 65536];
  unsigned box[NCTA * NKV * 32];
  int ovf[NCTA * 1280];
};
__device__ __align__(1024) Scratch g_scratch;
#define STAMPIF(c, i)
#define GSTAMPIF(c, i)
#define PROF_DUMP()

constexpr uint32_t DESC_HI = 0x40000100u;
__device__ __forceinline__ void wgmma_qk64(float (&d)[40], uint64_t da, uint64_t db, int sd) {
  asm volatile("{\n.reg .pred p;\nsetp.ne.b32 p, %42, 0;\n"
    "wgmma.mma_async.sync.aligned.m64n80k16.f32.bf16.bf16 {%0, %1, %2, %3, %4, %5, %6, %7, %8, %9, %10, %11, %12, %13, %14, %15, %16, %17, %18, %19, %20, %21, %22, %23, %24, %25, %26, %27, %28, %29, %30, %31, %32, %33, %34, %35, %36, %37, %38, %39}, %40, %41, p, 1, 1, 0, 0;\n}\n"
    : "+f"(d[0]), "+f"(d[1]), "+f"(d[2]), "+f"(d[3]), "+f"(d[4]), "+f"(d[5]), "+f"(d[6]), "+f"(d[7]), "+f"(d[8]), "+f"(d[9]), "+f"(d[10]), "+f"(d[11]), "+f"(d[12]), "+f"(d[13]), "+f"(d[14]), "+f"(d[15]), "+f"(d[16]), "+f"(d[17]), "+f"(d[18]), "+f"(d[19]), "+f"(d[20]), "+f"(d[21]), "+f"(d[22]), "+f"(d[23]), "+f"(d[24]), "+f"(d[25]), "+f"(d[26]), "+f"(d[27]), "+f"(d[28]), "+f"(d[29]), "+f"(d[30]), "+f"(d[31]), "+f"(d[32]), "+f"(d[33]), "+f"(d[34]), "+f"(d[35]), "+f"(d[36]), "+f"(d[37]), "+f"(d[38]), "+f"(d[39])
    : "l"(da), "l"(db), "r"(sd));
}

__device__ __forceinline__ void wgmma_qkr64(float (&d)[40], uint32_t a0, uint32_t a1, uint32_t a2, uint32_t a3, uint64_t db, int sd) {
  asm volatile("{\n.reg .pred p;\nsetp.ne.b32 p, %45, 0;\n"
    "wgmma.mma_async.sync.aligned.m64n80k16.f32.bf16.bf16 {%0, %1, %2, %3, %4, %5, %6, %7, %8, %9, %10, %11, %12, %13, %14, %15, %16, %17, %18, %19, %20, %21, %22, %23, %24, %25, %26, %27, %28, %29, %30, %31, %32, %33, %34, %35, %36, %37, %38, %39}, {%40, %41, %42, %43}, %44, p, 1, 1, 0;\n}\n"
    : "+f"(d[0]), "+f"(d[1]), "+f"(d[2]), "+f"(d[3]), "+f"(d[4]), "+f"(d[5]), "+f"(d[6]), "+f"(d[7]), "+f"(d[8]), "+f"(d[9]), "+f"(d[10]), "+f"(d[11]), "+f"(d[12]), "+f"(d[13]), "+f"(d[14]), "+f"(d[15]), "+f"(d[16]), "+f"(d[17]), "+f"(d[18]), "+f"(d[19]), "+f"(d[20]), "+f"(d[21]), "+f"(d[22]), "+f"(d[23]), "+f"(d[24]), "+f"(d[25]), "+f"(d[26]), "+f"(d[27]), "+f"(d[28]), "+f"(d[29]), "+f"(d[30]), "+f"(d[31]), "+f"(d[32]), "+f"(d[33]), "+f"(d[34]), "+f"(d[35]), "+f"(d[36]), "+f"(d[37]), "+f"(d[38]), "+f"(d[39])
    : "r"(a0), "r"(a1), "r"(a2), "r"(a3), "l"(db), "r"(sd));
}

__device__ __forceinline__ void wgmma_pv64(float (&d)[128], uint32_t a0, uint32_t a1, uint32_t a2, uint32_t a3, uint64_t db, int sd) {
  asm volatile("{\n.reg .pred p;\nsetp.ne.b32 p, %133, 0;\n"
    "wgmma.mma_async.sync.aligned.m64n256k16.f32.bf16.bf16 {%0, %1, %2, %3, %4, %5, %6, %7, %8, %9, %10, %11, %12, %13, %14, %15, %16, %17, %18, %19, %20, %21, %22, %23, %24, %25, %26, %27, %28, %29, %30, %31, %32, %33, %34, %35, %36, %37, %38, %39, %40, %41, %42, %43, %44, %45, %46, %47, %48, %49, %50, %51, %52, %53, %54, %55, %56, %57, %58, %59, %60, %61, %62, %63, %64, %65, %66, %67, %68, %69, %70, %71, %72, %73, %74, %75, %76, %77, %78, %79, %80, %81, %82, %83, %84, %85, %86, %87, %88, %89, %90, %91, %92, %93, %94, %95, %96, %97, %98, %99, %100, %101, %102, %103, %104, %105, %106, %107, %108, %109, %110, %111, %112, %113, %114, %115, %116, %117, %118, %119, %120, %121, %122, %123, %124, %125, %126, %127}, {%128, %129, %130, %131}, %132, p, 1, 1, 1;\n}\n"
    : "+f"(d[0]), "+f"(d[1]), "+f"(d[2]), "+f"(d[3]), "+f"(d[4]), "+f"(d[5]), "+f"(d[6]), "+f"(d[7]), "+f"(d[8]), "+f"(d[9]), "+f"(d[10]), "+f"(d[11]), "+f"(d[12]), "+f"(d[13]), "+f"(d[14]), "+f"(d[15]), "+f"(d[16]), "+f"(d[17]), "+f"(d[18]), "+f"(d[19]), "+f"(d[20]), "+f"(d[21]), "+f"(d[22]), "+f"(d[23]), "+f"(d[24]), "+f"(d[25]), "+f"(d[26]), "+f"(d[27]), "+f"(d[28]), "+f"(d[29]), "+f"(d[30]), "+f"(d[31]), "+f"(d[32]), "+f"(d[33]), "+f"(d[34]), "+f"(d[35]), "+f"(d[36]), "+f"(d[37]), "+f"(d[38]), "+f"(d[39]), "+f"(d[40]), "+f"(d[41]), "+f"(d[42]), "+f"(d[43]), "+f"(d[44]), "+f"(d[45]), "+f"(d[46]), "+f"(d[47]), "+f"(d[48]), "+f"(d[49]), "+f"(d[50]), "+f"(d[51]), "+f"(d[52]), "+f"(d[53]), "+f"(d[54]), "+f"(d[55]), "+f"(d[56]), "+f"(d[57]), "+f"(d[58]), "+f"(d[59]), "+f"(d[60]), "+f"(d[61]), "+f"(d[62]), "+f"(d[63]), "+f"(d[64]), "+f"(d[65]), "+f"(d[66]), "+f"(d[67]), "+f"(d[68]), "+f"(d[69]), "+f"(d[70]), "+f"(d[71]), "+f"(d[72]), "+f"(d[73]), "+f"(d[74]), "+f"(d[75]), "+f"(d[76]), "+f"(d[77]), "+f"(d[78]), "+f"(d[79]), "+f"(d[80]), "+f"(d[81]), "+f"(d[82]), "+f"(d[83]), "+f"(d[84]), "+f"(d[85]), "+f"(d[86]), "+f"(d[87]), "+f"(d[88]), "+f"(d[89]), "+f"(d[90]), "+f"(d[91]), "+f"(d[92]), "+f"(d[93]), "+f"(d[94]), "+f"(d[95]), "+f"(d[96]), "+f"(d[97]), "+f"(d[98]), "+f"(d[99]), "+f"(d[100]), "+f"(d[101]), "+f"(d[102]), "+f"(d[103]), "+f"(d[104]), "+f"(d[105]), "+f"(d[106]), "+f"(d[107]), "+f"(d[108]), "+f"(d[109]), "+f"(d[110]), "+f"(d[111]), "+f"(d[112]), "+f"(d[113]), "+f"(d[114]), "+f"(d[115]), "+f"(d[116]), "+f"(d[117]), "+f"(d[118]), "+f"(d[119]), "+f"(d[120]), "+f"(d[121]), "+f"(d[122]), "+f"(d[123]), "+f"(d[124]), "+f"(d[125]), "+f"(d[126]), "+f"(d[127])
    : "r"(a0), "r"(a1), "r"(a2), "r"(a3), "l"(db), "r"(sd));
}

__device__ __forceinline__ void wgmma_qk(float (&d)[40], uint32_t da, uint32_t db, int sd) {
  asm volatile("{\n.reg .pred p;\n.reg .b64 da, db;\nmov.b64 da, {%40, %43};\nmov.b64 db, {%41, %43};\nsetp.ne.b32 p, %42, 0;\n"
    "wgmma.mma_async.sync.aligned.m64n80k16.f32.bf16.bf16 {%0, %1, %2, %3, %4, %5, %6, %7, %8, %9, %10, %11, %12, %13, %14, %15, %16, %17, %18, %19, %20, %21, %22, %23, %24, %25, %26, %27, %28, %29, %30, %31, %32, %33, %34, %35, %36, %37, %38, %39}, da, db, p, 1, 1, 0, 0;\n}\n"
    : "+f"(d[0]), "+f"(d[1]), "+f"(d[2]), "+f"(d[3]), "+f"(d[4]), "+f"(d[5]), "+f"(d[6]), "+f"(d[7]), "+f"(d[8]), "+f"(d[9]), "+f"(d[10]), "+f"(d[11]), "+f"(d[12]), "+f"(d[13]), "+f"(d[14]), "+f"(d[15]), "+f"(d[16]), "+f"(d[17]), "+f"(d[18]), "+f"(d[19]), "+f"(d[20]), "+f"(d[21]), "+f"(d[22]), "+f"(d[23]), "+f"(d[24]), "+f"(d[25]), "+f"(d[26]), "+f"(d[27]), "+f"(d[28]), "+f"(d[29]), "+f"(d[30]), "+f"(d[31]), "+f"(d[32]), "+f"(d[33]), "+f"(d[34]), "+f"(d[35]), "+f"(d[36]), "+f"(d[37]), "+f"(d[38]), "+f"(d[39])
    : "r"(da), "r"(db), "r"(sd), "r"(DESC_HI));
}

__device__ __forceinline__ void wgmma_rs256(float (&d)[128], uint32_t a0, uint32_t a1, uint32_t a2, uint32_t a3, uint32_t db, int sd) {
  asm volatile("{\n.reg .pred p;\n.reg .b64 da, db;\nmov.b64 db, {%132, %134};\nsetp.ne.b32 p, %133, 0;\n"
    "wgmma.mma_async.sync.aligned.m64n256k16.f32.bf16.bf16 {%0, %1, %2, %3, %4, %5, %6, %7, %8, %9, %10, %11, %12, %13, %14, %15, %16, %17, %18, %19, %20, %21, %22, %23, %24, %25, %26, %27, %28, %29, %30, %31, %32, %33, %34, %35, %36, %37, %38, %39, %40, %41, %42, %43, %44, %45, %46, %47, %48, %49, %50, %51, %52, %53, %54, %55, %56, %57, %58, %59, %60, %61, %62, %63, %64, %65, %66, %67, %68, %69, %70, %71, %72, %73, %74, %75, %76, %77, %78, %79, %80, %81, %82, %83, %84, %85, %86, %87, %88, %89, %90, %91, %92, %93, %94, %95, %96, %97, %98, %99, %100, %101, %102, %103, %104, %105, %106, %107, %108, %109, %110, %111, %112, %113, %114, %115, %116, %117, %118, %119, %120, %121, %122, %123, %124, %125, %126, %127}, {%128, %129, %130, %131}, db, p, 1, 1, 1;\n}\n"
    : "+f"(d[0]), "+f"(d[1]), "+f"(d[2]), "+f"(d[3]), "+f"(d[4]), "+f"(d[5]), "+f"(d[6]), "+f"(d[7]), "+f"(d[8]), "+f"(d[9]), "+f"(d[10]), "+f"(d[11]), "+f"(d[12]), "+f"(d[13]), "+f"(d[14]), "+f"(d[15]), "+f"(d[16]), "+f"(d[17]), "+f"(d[18]), "+f"(d[19]), "+f"(d[20]), "+f"(d[21]), "+f"(d[22]), "+f"(d[23]), "+f"(d[24]), "+f"(d[25]), "+f"(d[26]), "+f"(d[27]), "+f"(d[28]), "+f"(d[29]), "+f"(d[30]), "+f"(d[31]), "+f"(d[32]), "+f"(d[33]), "+f"(d[34]), "+f"(d[35]), "+f"(d[36]), "+f"(d[37]), "+f"(d[38]), "+f"(d[39]), "+f"(d[40]), "+f"(d[41]), "+f"(d[42]), "+f"(d[43]), "+f"(d[44]), "+f"(d[45]), "+f"(d[46]), "+f"(d[47]), "+f"(d[48]), "+f"(d[49]), "+f"(d[50]), "+f"(d[51]), "+f"(d[52]), "+f"(d[53]), "+f"(d[54]), "+f"(d[55]), "+f"(d[56]), "+f"(d[57]), "+f"(d[58]), "+f"(d[59]), "+f"(d[60]), "+f"(d[61]), "+f"(d[62]), "+f"(d[63]), "+f"(d[64]), "+f"(d[65]), "+f"(d[66]), "+f"(d[67]), "+f"(d[68]), "+f"(d[69]), "+f"(d[70]), "+f"(d[71]), "+f"(d[72]), "+f"(d[73]), "+f"(d[74]), "+f"(d[75]), "+f"(d[76]), "+f"(d[77]), "+f"(d[78]), "+f"(d[79]), "+f"(d[80]), "+f"(d[81]), "+f"(d[82]), "+f"(d[83]), "+f"(d[84]), "+f"(d[85]), "+f"(d[86]), "+f"(d[87]), "+f"(d[88]), "+f"(d[89]), "+f"(d[90]), "+f"(d[91]), "+f"(d[92]), "+f"(d[93]), "+f"(d[94]), "+f"(d[95]), "+f"(d[96]), "+f"(d[97]), "+f"(d[98]), "+f"(d[99]), "+f"(d[100]), "+f"(d[101]), "+f"(d[102]), "+f"(d[103]), "+f"(d[104]), "+f"(d[105]), "+f"(d[106]), "+f"(d[107]), "+f"(d[108]), "+f"(d[109]), "+f"(d[110]), "+f"(d[111]), "+f"(d[112]), "+f"(d[113]), "+f"(d[114]), "+f"(d[115]), "+f"(d[116]), "+f"(d[117]), "+f"(d[118]), "+f"(d[119]), "+f"(d[120]), "+f"(d[121]), "+f"(d[122]), "+f"(d[123]), "+f"(d[124]), "+f"(d[125]), "+f"(d[126]), "+f"(d[127])
    : "r"(a0), "r"(a1), "r"(a2), "r"(a3), "r"(db), "r"(sd), "r"(DESC_HI));
}

__device__ __forceinline__ void wgmma_ss256(float (&d)[128], uint32_t da, uint32_t db, int sd) {
  asm volatile("{\n.reg .pred p;\n.reg .b64 da, db;\nmov.b64 da, {%128, %131};\nmov.b64 db, {%129, %131};\nsetp.ne.b32 p, %130, 0;\n"
    "wgmma.mma_async.sync.aligned.m64n256k16.f32.bf16.bf16 {%0, %1, %2, %3, %4, %5, %6, %7, %8, %9, %10, %11, %12, %13, %14, %15, %16, %17, %18, %19, %20, %21, %22, %23, %24, %25, %26, %27, %28, %29, %30, %31, %32, %33, %34, %35, %36, %37, %38, %39, %40, %41, %42, %43, %44, %45, %46, %47, %48, %49, %50, %51, %52, %53, %54, %55, %56, %57, %58, %59, %60, %61, %62, %63, %64, %65, %66, %67, %68, %69, %70, %71, %72, %73, %74, %75, %76, %77, %78, %79, %80, %81, %82, %83, %84, %85, %86, %87, %88, %89, %90, %91, %92, %93, %94, %95, %96, %97, %98, %99, %100, %101, %102, %103, %104, %105, %106, %107, %108, %109, %110, %111, %112, %113, %114, %115, %116, %117, %118, %119, %120, %121, %122, %123, %124, %125, %126, %127}, da, db, p, 1, 1, 0, 1;\n}\n"
    : "+f"(d[0]), "+f"(d[1]), "+f"(d[2]), "+f"(d[3]), "+f"(d[4]), "+f"(d[5]), "+f"(d[6]), "+f"(d[7]), "+f"(d[8]), "+f"(d[9]), "+f"(d[10]), "+f"(d[11]), "+f"(d[12]), "+f"(d[13]), "+f"(d[14]), "+f"(d[15]), "+f"(d[16]), "+f"(d[17]), "+f"(d[18]), "+f"(d[19]), "+f"(d[20]), "+f"(d[21]), "+f"(d[22]), "+f"(d[23]), "+f"(d[24]), "+f"(d[25]), "+f"(d[26]), "+f"(d[27]), "+f"(d[28]), "+f"(d[29]), "+f"(d[30]), "+f"(d[31]), "+f"(d[32]), "+f"(d[33]), "+f"(d[34]), "+f"(d[35]), "+f"(d[36]), "+f"(d[37]), "+f"(d[38]), "+f"(d[39]), "+f"(d[40]), "+f"(d[41]), "+f"(d[42]), "+f"(d[43]), "+f"(d[44]), "+f"(d[45]), "+f"(d[46]), "+f"(d[47]), "+f"(d[48]), "+f"(d[49]), "+f"(d[50]), "+f"(d[51]), "+f"(d[52]), "+f"(d[53]), "+f"(d[54]), "+f"(d[55]), "+f"(d[56]), "+f"(d[57]), "+f"(d[58]), "+f"(d[59]), "+f"(d[60]), "+f"(d[61]), "+f"(d[62]), "+f"(d[63]), "+f"(d[64]), "+f"(d[65]), "+f"(d[66]), "+f"(d[67]), "+f"(d[68]), "+f"(d[69]), "+f"(d[70]), "+f"(d[71]), "+f"(d[72]), "+f"(d[73]), "+f"(d[74]), "+f"(d[75]), "+f"(d[76]), "+f"(d[77]), "+f"(d[78]), "+f"(d[79]), "+f"(d[80]), "+f"(d[81]), "+f"(d[82]), "+f"(d[83]), "+f"(d[84]), "+f"(d[85]), "+f"(d[86]), "+f"(d[87]), "+f"(d[88]), "+f"(d[89]), "+f"(d[90]), "+f"(d[91]), "+f"(d[92]), "+f"(d[93]), "+f"(d[94]), "+f"(d[95]), "+f"(d[96]), "+f"(d[97]), "+f"(d[98]), "+f"(d[99]), "+f"(d[100]), "+f"(d[101]), "+f"(d[102]), "+f"(d[103]), "+f"(d[104]), "+f"(d[105]), "+f"(d[106]), "+f"(d[107]), "+f"(d[108]), "+f"(d[109]), "+f"(d[110]), "+f"(d[111]), "+f"(d[112]), "+f"(d[113]), "+f"(d[114]), "+f"(d[115]), "+f"(d[116]), "+f"(d[117]), "+f"(d[118]), "+f"(d[119]), "+f"(d[120]), "+f"(d[121]), "+f"(d[122]), "+f"(d[123]), "+f"(d[124]), "+f"(d[125]), "+f"(d[126]), "+f"(d[127])
    : "r"(da), "r"(db), "r"(sd), "r"(DESC_HI));
}

__device__ __forceinline__ void wgmma_qkr(float (&d)[40], uint32_t a0, uint32_t a1, uint32_t a2, uint32_t a3, uint32_t db, int sd) {
  asm volatile("{\n.reg .pred p;\n.reg .b64 da, db;\nmov.b64 db, {%44, %46};\nsetp.ne.b32 p, %45, 0;\n"
    "wgmma.mma_async.sync.aligned.m64n80k16.f32.bf16.bf16 {%0, %1, %2, %3, %4, %5, %6, %7, %8, %9, %10, %11, %12, %13, %14, %15, %16, %17, %18, %19, %20, %21, %22, %23, %24, %25, %26, %27, %28, %29, %30, %31, %32, %33, %34, %35, %36, %37, %38, %39}, {%40, %41, %42, %43}, db, p, 1, 1, 0;\n}\n"
    : "+f"(d[0]), "+f"(d[1]), "+f"(d[2]), "+f"(d[3]), "+f"(d[4]), "+f"(d[5]), "+f"(d[6]), "+f"(d[7]), "+f"(d[8]), "+f"(d[9]), "+f"(d[10]), "+f"(d[11]), "+f"(d[12]), "+f"(d[13]), "+f"(d[14]), "+f"(d[15]), "+f"(d[16]), "+f"(d[17]), "+f"(d[18]), "+f"(d[19]), "+f"(d[20]), "+f"(d[21]), "+f"(d[22]), "+f"(d[23]), "+f"(d[24]), "+f"(d[25]), "+f"(d[26]), "+f"(d[27]), "+f"(d[28]), "+f"(d[29]), "+f"(d[30]), "+f"(d[31]), "+f"(d[32]), "+f"(d[33]), "+f"(d[34]), "+f"(d[35]), "+f"(d[36]), "+f"(d[37]), "+f"(d[38]), "+f"(d[39])
    : "r"(a0), "r"(a1), "r"(a2), "r"(a3), "r"(db), "r"(sd), "r"(DESC_HI));
}

__device__ __forceinline__ void wgmma_rs40(float (&d)[20], uint32_t a0, uint32_t a1, uint32_t a2, uint32_t a3, uint32_t db, int sd) {
  asm volatile("{\n.reg .pred p;\n.reg .b64 da, db;\nmov.b64 db, {%24, %26};\nsetp.ne.b32 p, %25, 0;\n"
    "wgmma.mma_async.sync.aligned.m64n40k16.f32.bf16.bf16 {%0, %1, %2, %3, %4, %5, %6, %7, %8, %9, %10, %11, %12, %13, %14, %15, %16, %17, %18, %19}, {%20, %21, %22, %23}, db, p, 1, 1, 0;\n}\n"
    : "+f"(d[0]), "+f"(d[1]), "+f"(d[2]), "+f"(d[3]), "+f"(d[4]), "+f"(d[5]), "+f"(d[6]), "+f"(d[7]), "+f"(d[8]), "+f"(d[9]), "+f"(d[10]), "+f"(d[11]), "+f"(d[12]), "+f"(d[13]), "+f"(d[14]), "+f"(d[15]), "+f"(d[16]), "+f"(d[17]), "+f"(d[18]), "+f"(d[19])
    : "r"(a0), "r"(a1), "r"(a2), "r"(a3), "r"(db), "r"(sd), "r"(DESC_HI));
}

__device__ __forceinline__ void wgmma_rs128(float (&d)[64], uint32_t a0, uint32_t a1, uint32_t a2, uint32_t a3, uint32_t db, int sd) {
  asm volatile("{\n.reg .pred p;\n.reg .b64 da, db;\nmov.b64 db, {%68, %70};\nsetp.ne.b32 p, %69, 0;\n"
    "wgmma.mma_async.sync.aligned.m64n128k16.f32.bf16.bf16 {%0, %1, %2, %3, %4, %5, %6, %7, %8, %9, %10, %11, %12, %13, %14, %15, %16, %17, %18, %19, %20, %21, %22, %23, %24, %25, %26, %27, %28, %29, %30, %31, %32, %33, %34, %35, %36, %37, %38, %39, %40, %41, %42, %43, %44, %45, %46, %47, %48, %49, %50, %51, %52, %53, %54, %55, %56, %57, %58, %59, %60, %61, %62, %63}, {%64, %65, %66, %67}, db, p, 1, 1, 1;\n}\n"
    : "+f"(d[0]), "+f"(d[1]), "+f"(d[2]), "+f"(d[3]), "+f"(d[4]), "+f"(d[5]), "+f"(d[6]), "+f"(d[7]), "+f"(d[8]), "+f"(d[9]), "+f"(d[10]), "+f"(d[11]), "+f"(d[12]), "+f"(d[13]), "+f"(d[14]), "+f"(d[15]), "+f"(d[16]), "+f"(d[17]), "+f"(d[18]), "+f"(d[19]), "+f"(d[20]), "+f"(d[21]), "+f"(d[22]), "+f"(d[23]), "+f"(d[24]), "+f"(d[25]), "+f"(d[26]), "+f"(d[27]), "+f"(d[28]), "+f"(d[29]), "+f"(d[30]), "+f"(d[31]), "+f"(d[32]), "+f"(d[33]), "+f"(d[34]), "+f"(d[35]), "+f"(d[36]), "+f"(d[37]), "+f"(d[38]), "+f"(d[39]), "+f"(d[40]), "+f"(d[41]), "+f"(d[42]), "+f"(d[43]), "+f"(d[44]), "+f"(d[45]), "+f"(d[46]), "+f"(d[47]), "+f"(d[48]), "+f"(d[49]), "+f"(d[50]), "+f"(d[51]), "+f"(d[52]), "+f"(d[53]), "+f"(d[54]), "+f"(d[55]), "+f"(d[56]), "+f"(d[57]), "+f"(d[58]), "+f"(d[59]), "+f"(d[60]), "+f"(d[61]), "+f"(d[62]), "+f"(d[63])
    : "r"(a0), "r"(a1), "r"(a2), "r"(a3), "r"(db), "r"(sd), "r"(DESC_HI));
}

__device__ __forceinline__ void wgmma_rs64t(float (&d)[32], uint32_t a0, uint32_t a1, uint32_t a2, uint32_t a3, uint32_t db, int sd) {
  asm volatile("{\n.reg .pred p;\n.reg .b64 da, db;\nmov.b64 db, {%36, %38};\nsetp.ne.b32 p, %37, 0;\n"
    "wgmma.mma_async.sync.aligned.m64n64k16.f32.bf16.bf16 {%0, %1, %2, %3, %4, %5, %6, %7, %8, %9, %10, %11, %12, %13, %14, %15, %16, %17, %18, %19, %20, %21, %22, %23, %24, %25, %26, %27, %28, %29, %30, %31}, {%32, %33, %34, %35}, db, p, 1, 1, 1;\n}\n"
    : "+f"(d[0]), "+f"(d[1]), "+f"(d[2]), "+f"(d[3]), "+f"(d[4]), "+f"(d[5]), "+f"(d[6]), "+f"(d[7]), "+f"(d[8]), "+f"(d[9]), "+f"(d[10]), "+f"(d[11]), "+f"(d[12]), "+f"(d[13]), "+f"(d[14]), "+f"(d[15]), "+f"(d[16]), "+f"(d[17]), "+f"(d[18]), "+f"(d[19]), "+f"(d[20]), "+f"(d[21]), "+f"(d[22]), "+f"(d[23]), "+f"(d[24]), "+f"(d[25]), "+f"(d[26]), "+f"(d[27]), "+f"(d[28]), "+f"(d[29]), "+f"(d[30]), "+f"(d[31])
    : "r"(a0), "r"(a1), "r"(a2), "r"(a3), "r"(db), "r"(sd), "r"(0x40000040u));
}

__device__ __forceinline__ uint32_t mkdesc(uint32_t addr, uint32_t lbo) { return ((addr & 0x3FFFF) >> 4) | ((lbo >> 4) << 16); }
#define WG_FENCE() asm volatile("wgmma.fence.sync.aligned;\n" ::: "memory")
#define WG_COMMIT() asm volatile("wgmma.commit_group.sync.aligned;\n" ::: "memory")
#define WG_WAIT(n) asm volatile("wgmma.wait_group.sync.aligned %0;\n" ::"n"(n) : "memory")
template <int N> __device__ __forceinline__ void pin(float (&d)[N]) {
#pragma unroll
  for (int i = 0; i < N; i++) asm volatile("" : "+f"(d[i])::"memory");
}
#define PROXY_FENCE() asm volatile("fence.proxy.async;\n" ::: "memory")
#define PROXY_FENCE_SMEM() asm volatile("fence.proxy.async.shared::cta;\n" ::: "memory")

__device__ __forceinline__ void mbar_init(uint32_t bar, uint32_t cnt) { asm volatile("mbarrier.init.shared::cta.b64 [%0], %1;\n" ::"r"(bar), "r"(cnt) : "memory"); }
__device__ __forceinline__ void mbar_expect_tx(uint32_t bar, uint32_t bytes) { asm volatile("mbarrier.arrive.expect_tx.shared::cta.b64 _, [%0], %1;\n" ::"r"(bar), "r"(bytes) : "memory"); }
__device__ __forceinline__ void mbar_arrive(uint32_t bar) { asm volatile("mbarrier.arrive.shared::cta.b64 _, [%0];\n" ::"r"(bar) : "memory"); }
__device__ __forceinline__ void mbar_wait(uint32_t bar, uint32_t parity) {
  asm volatile("{\n.reg .pred p;\n.reg .u32 n;\n.reg .u64 z;\nmov.u64 z, 0;\nmov.u32 n, 0;\n"
               "LAB_WAIT:\n"
               "mbarrier.try_wait.parity.shared::cta.b64 p, [%0], %1;\n"
               "@p bra LAB_DONE;\n"
               "add.u32 n, n, 1;\n"
               "setp.gt.u32 p, n, 20000000;\n"
               "@p st.global.u32 [z], n;\n"
               "bra LAB_WAIT;\n"
               "LAB_DONE:\n}\n" ::"r"(bar), "r"(parity) : "memory");
}
__device__ __forceinline__ void gwait(const unsigned* p, unsigned target) {
  asm volatile("{\n.reg .pred p;\n.reg .u32 n, v;\n.reg .u64 z;\nmov.u64 z, 0;\nmov.u32 n, 0;\n"
               "LAB_WAIT:\n"
               "ld.acquire.gpu.global.u32 v, [%0];\n"
               "sub.u32 v, v, %1;\n"
               "setp.ge.s32 p, v, 0;\n"
               "@p bra LAB_DONE;\n"
               "add.u32 n, n, 1;\n"
               "setp.gt.u32 p, n, 4000000;\n"
               "@p st.global.u32 [z], n;\n"
               "bra LAB_WAIT;\n"
               "LAB_DONE:\n}\n" ::"l"(p), "r"(target) : "memory");
}
#define GPU_FENCE() asm volatile("fence.acq_rel.gpu;\n" ::: "memory")
__device__ __forceinline__ void garrive(unsigned* p) { asm volatile("red.release.gpu.global.add.u32 [%0], 1;\n" ::"l"(p) : "memory"); }
__device__ __forceinline__ void garrive_relaxed(unsigned* p) { asm volatile("red.relaxed.gpu.global.add.u32 [%0], 1;\n" ::"l"(p) : "memory"); }
__device__ __forceinline__ void gset(unsigned* p, unsigned v) { asm volatile("st.release.gpu.global.u32 [%0], %1;\n" ::"l"(p), "r"(v) : "memory"); }
__device__ __forceinline__ void bulk_g2s(uint32_t dst, const void* src, uint32_t bytes, uint32_t bar) {
  asm volatile("cp.async.bulk.shared::cluster.global.mbarrier::complete_tx::bytes [%0], [%1], %2, [%3];\n" ::"r"(dst), "l"(src), "r"(bytes), "r"(bar) : "memory");
}
template <class T> __device__ __forceinline__ uint8_t* at(T* p, uint32_t off) {
  uint64_t r;
  asm("{\n.reg .u32 lo, hi;\nmov.b64 {lo, hi}, %1;\nadd.cc.u32 lo, lo, %2;\naddc.u32 hi, hi, 0;\nmov.b64 %0, {lo, hi};\n}" : "=l"(r) : "l"(p), "r"(off));
  return (uint8_t*)r;
}
__device__ __forceinline__ void bar_sync(int id, int n) { asm volatile("bar.sync %0, %1;\n" ::"r"(id), "r"(n) : "memory"); }
__device__ __forceinline__ void bar_arrive(int id, int n) { asm volatile("bar.arrive %0, %1;\n" ::"r"(id), "r"(n) : "memory"); }
__device__ __forceinline__ float ex2(float x) { float y; asm("ex2.approx.ftz.f32 %0, %1;" : "=f"(y) : "f"(x)); return y; }
__device__ __forceinline__ float rcp(float x) { float y; asm volatile("rcp.approx.ftz.f32 %0, %1;" : "=f"(y) : "f"(x)); return y; }
__device__ __forceinline__ float rsq(float x) { float y; asm("rsqrt.approx.ftz.f32 %0, %1;" : "=f"(y) : "f"(x)); return y; }
__device__ __forceinline__ uint32_t pack2(float lo, float hi) { uint32_t r; asm("cvt.rn.bf16x2.f32 %0, %1, %2;" : "=r"(r) : "f"(hi), "f"(lo)); return r; }
__device__ __forceinline__ float blo(uint32_t v) { return __uint_as_float(v << 16); }
__device__ __forceinline__ float bhi(uint32_t v) { return __uint_as_float(v & 0xffff0000u); }
__device__ __forceinline__ uint4 ldg_nc(const void* p) { uint4 v; asm volatile("ld.global.nc.v4.u32 {%0,%1,%2,%3}, [%4];" : "=r"(v.x), "=r"(v.y), "=r"(v.z), "=r"(v.w) : "l"(p)); return v; }
__device__ __forceinline__ uint4 ldg_cg(const void* p) { uint4 v; asm volatile("ld.global.cg.v4.u32 {%0,%1,%2,%3}, [%4];" : "=r"(v.x), "=r"(v.y), "=r"(v.z), "=r"(v.w) : "l"(p) : "memory"); return v; }
__device__ __forceinline__ void stg128(void* p, uint32_t a, uint32_t b, uint32_t c, uint32_t d) { asm volatile("st.global.v4.u32 [%0], {%1,%2,%3,%4};" ::"l"(p), "r"(a), "r"(b), "r"(c), "r"(d) : "memory"); }
__device__ __forceinline__ void sts128(uint32_t p, uint32_t a, uint32_t b, uint32_t c, uint32_t d) { asm volatile("st.shared.v4.u32 [%0], {%1,%2,%3,%4};" ::"r"(p), "r"(a), "r"(b), "r"(c), "r"(d) : "memory"); }
__device__ __forceinline__ uint4 lds128(uint32_t p) { uint4 v; asm volatile("ld.shared.v4.u32 {%0,%1,%2,%3}, [%4];" : "=r"(v.x), "=r"(v.y), "=r"(v.z), "=r"(v.w) : "r"(p) : "memory"); return v; }
__device__ __forceinline__ float quad_sum(float v) { v += __shfl_xor_sync(~0u, v, 1); return v + __shfl_xor_sync(~0u, v, 2); }
__device__ __forceinline__ float quad_max(float v) { v = fmaxf(v, __shfl_xor_sync(~0u, v, 1)); return fmaxf(v, __shfl_xor_sync(~0u, v, 2)); }
__device__ __forceinline__ void mma16816(float (&d)[4], uint32_t a0, uint32_t a1, uint32_t a2, uint32_t a3, uint32_t b0, uint32_t b1) {
  asm("mma.sync.aligned.m16n8k16.row.col.f32.bf16.bf16.f32 {%0,%1,%2,%3}, {%4,%5,%6,%7}, {%8,%9}, {%0,%1,%2,%3};"
               : "+f"(d[0]), "+f"(d[1]), "+f"(d[2]), "+f"(d[3]) : "r"(a0), "r"(a1), "r"(a2), "r"(a3), "r"(b0), "r"(b1));
}
__device__ __forceinline__ uint32_t comp(const uint4& v, int i) { return i == 0 ? v.x : i == 1 ? v.y : i == 2 ? v.z : v.w; }
__device__ __forceinline__ void bulk_s2g(void* dst, uint32_t src, uint32_t bytes) {
  asm volatile("cp.async.bulk.global.shared::cta.bulk_group [%0], [%1], %2;\n" ::"l"(dst), "r"(src), "r"(bytes) : "memory");
}
__device__ __forceinline__ void bulk_red(void* dst, uint32_t src, uint32_t bytes) {
  asm volatile("cp.reduce.async.bulk.global.shared::cta.bulk_group.add.noftz.bf16 [%0], [%1], %2;\n" ::"l"(dst), "r"(src), "r"(bytes) : "memory");
}
#define BULK_COMMIT() asm volatile("cp.async.bulk.commit_group;\n" ::: "memory")
#define BULK_WAIT_READ() asm volatile("cp.async.bulk.wait_group.read 0;\n" ::: "memory")
#define BULK_WAIT() asm volatile("cp.async.bulk.wait_group 0;\n" ::: "memory")
__device__ __forceinline__ void cp16(uint32_t dst, const void* src) { asm volatile("cp.async.cg.shared.global [%0], [%1], 16;\n" ::"r"(dst), "l"(src) : "memory"); }
__device__ __forceinline__ void ldsm4(uint32_t (&r)[4], uint32_t p) {
  asm volatile("ldmatrix.sync.aligned.m8n8.x4.shared.b16 {%0,%1,%2,%3}, [%4];" : "=r"(r[0]), "=r"(r[1]), "=r"(r[2]), "=r"(r[3]) : "r"(p));
}
__device__ __forceinline__ void stsm4(uint32_t p, uint32_t a, uint32_t b, uint32_t c, uint32_t d) {
  asm volatile("stmatrix.sync.aligned.m8n8.x4.shared.b16 [%0], {%1,%2,%3,%4};" ::"r"(p), "r"(a), "r"(b), "r"(c), "r"(d) : "memory");
}
__device__ __forceinline__ uint32_t hfma2(uint32_t a, uint32_t b, uint32_t c) { uint32_t r; asm("fma.rn.bf16x2 %0, %1, %2, %3;" : "=r"(r) : "r"(a), "r"(b), "r"(c)); return r; }
__device__ __forceinline__ uint32_t hadd2(uint32_t a, uint32_t b) { uint32_t r; asm("add.rn.bf16x2 %0, %1, %2;" : "=r"(r) : "r"(a), "r"(b)); return r; }

__device__ __forceinline__ void product_load(const bool qk, const bool kperm, const __nv_bfloat16* __restrict__ L, const __nv_bfloat16* __restrict__ R,
                                             int d0, int c0, uint32_t sm) {
  const int ch = threadIdx.x & 31, w = threadIdx.x >> 5;
  const uint32_t smr = sm + 40 * 512;
  const __nv_bfloat16* lp = L + (d0 + (kperm ? ((w & 6) << 2) | (w & 1) : w)) * 256 + ch * 8;
  const uint32_t ls = sm + w * 512 + ((ch ^ w) << 4);
#pragma unroll
  for (int i = 0; i < 4; i++) cp16(ls + i * 4096, lp + i * (kperm ? 512 : 2048));
  cp16(ls + 4 * 4096, L + (248 + w) * 256 + ch * 8);
  if (qk) {
    const uint32_t rs = smr + (ch >> 3) * 1024 + w * 128 + (((ch ^ w) & 7) << 4);
#pragma unroll
    for (int i = 0; i < 4; i++) cp16(rs + i * 4096, R + (c0 + w + i * 8) * 256 + ch * 8);
    cp16(rs + 4 * 4096, R + (248 + w) * 256 + ch * 8);
  } else {
    const int e = w * 4 + (ch >> 3);
#pragma unroll
    for (int i = 0; i < 8; i++) cp16(smr + (e + i * 32) * 128 + (((ch ^ e) & 7) << 4), R + (e + i * 32) * 256 + c0 + (ch & 7) * 8);
  }
}
template <bool qk>
__device__ __forceinline__ void product_mma(uint8_t* img, int d0, int c0, uint32_t sm) {
  const int lane = threadIdx.x & 31, w = (threadIdx.x >> 5) & 3, l7 = lane & 7;
  const uint32_t pa = sm + (((lane & 8) ? 32 : w * 8) + l7) * 512;
  const uint32_t bd = mkdesc(sm + 40 * 512, 16);
  uint32_t a[16][4];
#pragma unroll
  for (int u = 0; u < 16; u++) ldsm4(a[u], pa + (u >> 2) * 128 + ((((u & 3) * 2 + (lane >> 4)) ^ l7) << 4));
  constexpr int NT = qk ? 4 : 8;
  float m[qk ? 20 : 32];
  pin(m);
  WG_FENCE();
#pragma unroll
  for (int u = 0; u < 16; u++) {
    if constexpr (qk) wgmma_rs40(m, a[u][0], a[u][1], a[u][2], a[u][3], bd + (u >> 2) * 64 + (u & 3) * 2, u);
    else wgmma_rs64t(m, a[u][0], a[u][1], a[u][2], a[u][3], bd + u * 128, u);
  }
  WG_COMMIT();
  WG_WAIT(0);
  pin(m);
  STAMPIF(threadIdx.x == 256, 27);
  float z = 0.f, u = 0.f;
  if constexpr (qk) { z = quad_sum(m[18] + m[19]); u = quad_sum(m[16] + m[17]); }
#pragma unroll
  for (int o = 4; o < 32; o *= 2) {
#pragma unroll
    for (int n = 0; n < NT; n++) { m[4 * n + 2] += __shfl_xor_sync(~0u, m[4 * n + 2], o); m[4 * n + 3] += __shfl_xor_sync(~0u, m[4 * n + 3], o); }
    if constexpr (qk) z += __shfl_xor_sync(~0u, z, o);
  }
  const int g = lane >> 2, t = lane & 3;
  u -= z * 0.125f;
  const float sc = d0 + w * 8 + g == 255 ? 0.f : qk ? 1.4426950408889634f / 16.f : 1.f;
  uint32_t v[NT];
#pragma unroll
  for (int n = 0; n < NT; n++) v[n] = pack2(fmaf(m[4 * n + 2] + u, -0.125f, m[4 * n]) * sc, fmaf(m[4 * n + 3] + u, -0.125f, m[4 * n + 1]) * sc);
  uint8_t* gp = img + ((d0 >> 3) + w) * 4096 + (c0 >> 6) * 1024 + g * 128;
  if constexpr (qk) {
    if (c0 == 224 && t == 3) v[3] &= 0xffffu;
    const uint32_t so = sm + 57344 + w * 1024;
    stsm4(so + l7 * 128 + (((lane >> 3) ^ l7) << 4), v[0], v[1], v[2], v[3]);
    __syncwarp();
    const uint4 r = lds128(so + g * 128 + ((t ^ g) << 4));
    stg128(gp + (((t + ((c0 >> 3) & 4)) ^ g) << 4), r.x, r.y, r.z, r.w);
  } else {
    stg128(gp + ((t ^ g) << 4), v[0], v[1], v[2], v[3]);
    stg128(gp + (((t + 4) ^ g) << 4), v[4], v[5], v[6], v[7]);
  }
}
__device__ __forceinline__ void product_done(unsigned* ctr) {
  STAMPIF(threadIdx.x == 256, 31);
  bar_sync(5, 128);
  if (threadIdx.x == (blockIdx.x < 64 ? 256 : 288)) garrive(ctr);
  STAMPIF(threadIdx.x == (blockIdx.x < 64 ? 256 : 288), 34);
  __syncwarp();
}

__global__ void __launch_bounds__(384, 1)
gps_kernel(const __nv_bfloat16* __restrict__ x, const int* __restrict__ src, const int* __restrict__ dst,
           const __nv_bfloat16* __restrict__ deg_inv, const __nv_bfloat16* __restrict__ w_msg,
           const __nv_bfloat16* __restrict__ wq, const __nv_bfloat16* __restrict__ wk, const __nv_bfloat16* __restrict__ wv,
           const __nv_bfloat16* __restrict__ w_out, __nv_bfloat16* __restrict__ out, Scratch* G) {
  extern __shared__ __align__(1024) uint8_t smem_raw[];
  const uint32_t sb = (uint32_t)__cvta_generic_to_shared(smem_raw);
  const uint32_t ring = sb + SM_RING, full0 = sb + SM_BAR, empty0 = full0 + 8 * NST, qbar0 = empty0 + 8 * NST;
  const uint32_t evt0 = qbar0 + 16, one0 = evt0 + 112;
  const uint32_t sfree = one0, wsent = one0 + 8, wfirst = one0 + 16, go = one0 + 24, bbar = one0 + 32, hread0 = one0 + 40, xbar0 = one0 + 56, cbar = one0 + 120, ebar = one0 + 128;
  const int wg = __shfl_sync(~0u, threadIdx.x >> 7, 0);
  const int lane = threadIdx.x & 31;
  const int cta = blockIdx.x;
  GSTAMPIF(threadIdx.x == 0, 0);
  const bool prod = cta < 126 || cta >= 130;
  const int pi = cta < 126 ? cta : cta - 4;
  const int kind = max((pi >> 5) - 1, 0), pd0 = ((pi >> (kind ? 2 : 3)) & 7) * 32, pc0 = kind ? (pi & 3) * 64 : (pi & 7) * 32;
  const bool early = cta > 125 && cta < 131;
  const int xfirst = cta == 130 ? 1 : early ? 4 : 0;
  const uint32_t cnt = sb + SM_META, box = sb + SM_AUX;
  const int e0 = cta * 1216, ne = min(E_ - e0, 1216);
  if (wg < 2) {
    if (prod) product_load(kind == 0, kind == 1, kind == 0 ? wq : kind == 1 ? w_msg : wv, kind == 0 ? wk : w_out, pd0, pc0, ring);
  } else if (threadIdx.x < 320) {
#pragma unroll 1
    for (int i = threadIdx.x - 256; i < 1024 + 32; i += 64) sts128(i < 1024 ? box + i * 16 : cnt + (i - 1024) * 16, 0, 0, 0, 0);
  } else if (threadIdx.x == 352) {
    cp16(sb + SM_BAR + 496, &G->epoch);
  } else if (threadIdx.x == 320) {
#pragma unroll
    for (int i = 0; i < 39; i++) mbar_init(full0 + 8 * i, i >= 3 && i < 6 ? 8 : i >= 8 && i < 22 ? 128 : i == 37 ? 384 : 1);
    asm volatile("fence.mbarrier_init.release.cluster;\n" ::: "memory");
    const int r = cta % 5, t0 = (cta / 5) * 3 + (r < 3 ? r : r - 2);
#pragma unroll 1
    for (int i = 0; i < xfirst; i++) {
      const int pc = r < 3 ? i : i ^ 4;
      mbar_expect_tx(xbar0 + 8 * i, 8192);
      bulk_g2s(sb + SM_Q + pc * 8192, x + (size_t)(t0 * 128 + pc * 16) * 256, 8192, xbar0 + 8 * i);
    }
  }
  STAMPIF(threadIdx.x == 128, 26);

  const int grp = cta / 5, role = cta < 130 ? cta - grp * 5 : (cta == 130 ? 1 : 5);
  const bool owner = role < 3;
  const int tA = grp * 3;
  int q0, n0, o0, q1 = 0, k1 = 0, n1 = 0, i1 = -1;
  if (cta >= 130) { q0 = 78; n0 = owner ? 64 : NKV - 64; o0 = 78; if (owner) i1 = 78; }
  else if (owner) { q0 = tA + role; n0 = role == 0 ? SCHED_A : role == 1 ? SCHED_B : SCHED_C; i1 = o0 = q0; }
  else if (role == 3) { q0 = tA + 1; n0 = SCHED_B1; o0 = NQT + grp; q1 = tA; k1 = SCHED_A; n1 = NKV - SCHED_A; }
  else { q0 = tA + 2; n0 = NKV - SCHED_C; o0 = q0; q1 = tA + 1; k1 = SCHED_B; n1 = NKV - SCHED_B - SCHED_B1; i1 = NQT + grp; }
  const int lu = (role == 3 ? tA : q0) * 2, lu2 = (tA + 1) * 2 + role - 3;

  const bool staged = role == 3;

  __syncthreads();
  asm volatile("cp.async.mbarrier.arrive.noinc.shared::cta.b64 [%0];\n" ::"r"(cbar) : "memory");

  if (wg == 2) {
    STAMPIF(threadIdx.x == 256, 40);
    mbar_wait(cbar, 0);
    if (prod) {
      PROXY_FENCE_SMEM();
      STAMPIF(threadIdx.x == 256, 24);
      if (kind == 0) product_mma<true>(G->w, pd0, pc0, ring); else product_mma<false>(G->w + kind * 131072, pd0, pc0, ring);
      product_done(&G->ctr[kind ? C_M : C_W]);
    }
    asm volatile("setmaxnreg.dec.sync.aligned.u32 56;\n");
    unsigned ep;
    asm volatile("ld.shared.u32 %0, [%1];" : "=r"(ep) : "r"(sb + SM_BAR + 496) : "memory");
    ep += 1;
    const int w = (threadIdx.x >> 5) & 3;
    if (w == 0) {
      if (lane == 0) {
        STAMPIF(true, 1);
        uint32_t st = 0, ph = 1;
        auto push = [&](const uint8_t* p, const uint8_t* rem) {
          mbar_wait(empty0 + 8 * st, ph);
          mbar_expect_tx(full0 + 8 * st, rem ? STB + 8192 : STB);
          bulk_g2s(ring + st * STB, p, STB, full0 + 8 * st);
          if (rem) bulk_g2s(sb + SM_REM, rem, 8192, full0 + 8 * st);
          if (++st == NST) { st = 0; ph ^= 1; }
        };
        auto qfill = [&](int e, int h, const uint8_t* p, const unsigned* flag, unsigned target, const float2* meta) {
          if (flag) gwait(flag, target);
          mbar_wait(evt0 + 16 * e + 8 * h, 0);
          PROXY_FENCE_SMEM();
          mbar_expect_tx(qbar0 + 8 * h, meta ? 32768 + 512 : 32768);
          bulk_g2s(sb + SM_Q + h * 32768, p + h * 32768, 32768, qbar0 + 8 * h);
          if (meta) bulk_g2s(sb + SM_META + h * 512, meta, 512, qbar0 + 8 * h);
        };
        auto lload = [&](int u, int blk, uint32_t dst) {
          const uint32_t lfull = xbar0 + 8 * u;
          const uint32_t nd = blk < 156 ? 128 : blk == 156 ? 32 : 0;
          mbar_expect_tx(lfull, 32768 + nd);
          bulk_g2s(dst, at(G->acc, blk * 32768), 32768, lfull);
          if (nd) bulk_g2s(sb + SM_DINV + u * 128, at(deg_inv, blk * 128), nd, lfull);
        };
        gwait(&G->ctr[C_W], ep * CNT_W);
        PROXY_FENCE_SMEM();
        STAMPIF(true, 2);
        mbar_expect_tx(wfirst, 16384);
        bulk_g2s(ring, G->w, 16384, wfirst);
        mbar_expect_tx(full0, STB - 16384);
        bulk_g2s(ring + 16384, G->w + 16384, STB - 16384, full0);
        st = 1;
#pragma unroll 1
        for (int i = 1; i < 3; i++) push(G->w + i * STB, i == 2 ? G->w + 3 * STB : nullptr);
        mbar_arrive(wsent);
        gwait(&G->ctr[C_E], ep * CNT_E);
        STAMPIF(true, 3);
        const int ntot = n0 + n1;
        int h1 = 1;
#pragma unroll 1
        for (int j = 0; j < ntot + 3; j++) {
          if (j == (owner ? 2 : 1)) gwait(&G->ctr[C_F], ep * CNT_F);
          if (j == 3) gwait(&G->ctr[C_H], ep * CNT_H);
          if (j == ntot) {
            gwait(&G->ctr[C_G], ep * CNT_G);
            PROXY_FENCE_SMEM();
            if (role == 4) lload(0, lu, sb + SM_AUX);
            if (role == 3) lload(2, lu2, sb + SM_AUX);
          }
          int kt = j >= n0 ? k1 + j - n0 : owner ? j : NKV - 1 - j;
          if (kt < 3) kt = kt == 2 ? 21 : 123 - kt; else if (kt >= 21 && kt < 24) kt -= 21; else if (kt == 122 || kt == 123) kt -= 100;
          const uint8_t* wp_ = G->w + (owner ? 262144 : 131072) + (j - ntot) * STB;
          push(j < ntot ? at(G->ht, kt * STB) : wp_, j == ntot ? wp_ + 3 * STB : nullptr);
          if (j == JBG) { mbar_arrive(qbar0); mbar_arrive(qbar0 + 8); }
          if (j == JSCAT) mbar_arrive(go);
          if (n1) {
            const int h = j - n0;
            if (h == 0 || h == 1) qfill(1, h, G->qt + (size_t)q1 * 65536, h ? nullptr : &G->ctr[C_M], ep * CNT_M, nullptr);
          }
          const int h = j - ntot;
          if (h == 1 && owner) {
            unsigned v, fr;
            do {
              asm volatile("{\n.reg .pred p;\nmbarrier.test_wait.parity.shared::cta.b64 p, [%1], %2;\nselp.u32 %0, 1, 0, p;\n}\n" : "=r"(fr) : "r"(empty0 + 8 * st), "r"(ph) : "memory");
              asm volatile("ld.acquire.gpu.global.u32 %0, [%1];" : "=r"(v) : "l"(at(G->pflag, i1 * 8 + 4)) : "memory");
            } while (v != ep && !fr);
            if (v != ep) h1 = 2;
          }
          if ((h == 0 || h == h1) && i1 >= 0)
            qfill(n1 ? 6 : 1, h != 0, G->part + (size_t)i1 * 65536, h == 1 && owner ? nullptr : (unsigned*)at(G->pflag, i1 * 8 + (h != 0) * 4), ep, &G->meta[i1 * 128 + (h != 0) * 64]);
          if ((h == 0 || h == 1) && i1 < 0) { mbar_wait(evt0 + (n1 ? 96 : 16) + 8 * h, 0); lload(h, lu + h, sb + SM_Q + h * 32768); }
        }
        if (role == 4) {
          mbar_wait(evt0 + 80, 0); PROXY_FENCE_SMEM(); mbar_wait(wsent, 1); lload(1, lu + 1, sb + SM_AUX);
          mbar_wait(evt0 + 88, 0); PROXY_FENCE_SMEM(); mbar_wait(wfirst, 1); lload(2, lu2, sb + SM_AUX);
        }
        if (cta == 0) G->epoch = ep;
      }
    } else {
      if (w == 3 && lane == 0) {
        const int pub = role == 0 ? 3 : owner ? 1 : 2;
        if (!early) mbar_wait(wsent, 0);
#pragma unroll 1
        for (int h = 0; h < 2; h++) {
          if (pub >> h & 1) { mbar_wait(evt0 + 64 + 8 * h, 0); bulk_s2g(G->ht + (size_t)q0 * 65536 + h * 32768, sb + SM_Q + h * 32768, cta >= 130 ? 8192 : pub == 3 && h ? 32768 - HSPLIT : 32768); }
          BULK_COMMIT();
        }
        asm volatile("cp.async.bulk.wait_group 1;\n" ::: "memory");
        mbar_arrive(hread0);
        if (pub == 3 && HSPLIT) {
          mbar_wait(empty0, 0);
          __nanosleep(50);
          bulk_s2g(G->ht + (size_t)q0 * 65536 + 65536 - HSPLIT, sb + SM_Q + 65536 - HSPLIT, HSPLIT);
          BULK_COMMIT();
        }
        BULK_WAIT();
        mbar_arrive(hread0 + 8);
        GPU_FENCE();
        if (early) garrive_relaxed(&G->ctr[C_E]);
        if (cta > 20 && cta < 25) garrive_relaxed(&G->ctr[C_F]);
        garrive_relaxed(&G->ctr[C_H]);
        STAMPIF(true, 30);
      }
      __syncwarp();
      mbar_wait(qbar0 + 8, 0);
      if (w < 3) {
        const uint32_t eb = box + 16384;
        if (threadIdx.x == 288) {
          mbar_expect_tx(ebar, ne * 8);
          bulk_g2s(eb, src + e0, ne * 4, ebar);
          bulk_g2s(eb + 8192, dst + e0, ne * 4, ebar);
        }
        __syncwarp();
        mbar_wait(ebar, 0);
#pragma unroll 1
        for (int i = threadIdx.x - 288; i < ne / 4; i += 64) {
          const uint4 vs = lds128(eb + i * 16), vd = lds128(eb + 8192 + i * 16);
          uint32_t tl[4], sl[4];
#pragma unroll
          for (int u = 0; u < 4; u++) {
            tl[u] = comp(vs, u) * 52429u >> 22;
            asm volatile("atom.shared.add.u32 %0, [%1], 1;" : "=r"(sl[u]) : "r"(cnt + tl[u] * 4) : "memory");
          }
#pragma unroll
          for (int u = 0; u < 4; u++)
            if (sl[u] < 32) asm volatile("st.shared.u32 [%0], %1;" ::"r"(box + tl[u] * 128 + sl[u] * 4), "r"(0x80000000u | (comp(vs, u) - tl[u] * BN) << 14 | comp(vd, u)) : "memory");
          if ((sl[0] | sl[1] | sl[2] | sl[3]) >= 32) {
#pragma unroll 1
            for (int u = 0; u < 4; u++) {
              const uint32_t a = u & 1 ? (u & 2 ? sl[3] : sl[1]) : (u & 2 ? sl[2] : sl[0]);
              if (a >= 32) {
                uint32_t k;
                asm volatile("atom.shared.add.u32 %0, [%1], 1;" : "=r"(k) : "r"(cnt + NKV * 4) : "memory");
                G->ovf[cta * 1280 + k] = comp(vs, u) << 14 | comp(vd, u);
              }
            }
          }
        }
        PROXY_FENCE_SMEM();
        STAMPIF(threadIdx.x == 288, 36);
        bar_arrive(8, 96);
      }
      if (w == 3) {
#pragma unroll 4
        for (int i = 0; i < 16; i++) sts128(sb + SM_REM + i * 512 + lane * 16, 0, 0, 0, 0);
        PROXY_FENCE_SMEM();
        bar_sync(8, 96);
        if (lane == 0) {
#pragma unroll 1
          for (int i = 0; i < 5; i++) {
            const size_t off = (size_t)cta * 40960 + i * 8192;
            if (cta < NKV) { mbar_expect_tx(bbar, 8192); bulk_g2s(box + 16384, (const uint8_t*)x + off, 8192, bbar); }
            bulk_s2g(G->acc + off, sb + SM_REM, 8192);
            if (cta < NKV) { mbar_wait(bbar, i & 1); bulk_s2g((uint8_t*)out + off, box + 16384, 8192); }
            BULK_COMMIT();
            BULK_WAIT();
          }
          if (cta < 130 && role < 2) {
            mbar_wait(evt0, 0);
            mbar_wait(evt0 + 8, 0);
#pragma unroll 1
            for (int i = 0; i < 8; i++) {
              bulk_s2g(G->qt + (size_t)q0 * 65536 + i * 8192, sb + SM_Q + i * 8192, 8192);
              BULK_COMMIT();
              BULK_WAIT();
            }
          }
        }
        __syncwarp();
        bar_arrive(6, 96);
        if (lane == 0 && !owner) {
#pragma unroll 1
          for (int u = n1 ? 0 : 2; u < 4; u++) {
            mbar_wait(evt0 + 32 + 8 * u, 0);
            if (staged && u == 0) {
              mbar_wait(evt0 + 40, 0);
#pragma unroll 1
              for (int i = 0; i < 10; i++) {
                bulk_s2g(G->part + (size_t)o0 * 65536 + (i < 5 ? i * 4096 : 12288 + i * 4096), sb + SM_REM + i * 4096, 4096);
                BULK_COMMIT();
                BULK_WAIT();
              }
              mbar_arrive(sfree);
            }
            gset(&G->pflag[(u < 2 || !n1 ? o0 : q1) * 2 + (u & 1)], ep);
            if (u >= 2) mbar_arrive(u == 2 ? wsent : wfirst);
          }
        }
      } else {
        bar_sync(6, 96);
        int novf;
        asm volatile("ld.shared.u32 %0, [%1];" : "=r"(novf) : "r"(cnt + NKV * 4) : "memory");
        if (threadIdx.x == 288) {
          bulk_s2g(G->box + cta * NKV * 32, box, NKV * 128);
          BULK_COMMIT();
          BULK_WAIT();
          garrive(&G->ctr[C_M]);
          STAMPIF(true, 43);
          gwait(&G->ctr[C_H], ep * CNT_H);
          if (staged) mbar_wait(sfree, 0);
          if (cta < NKV) { mbar_expect_tx(bbar, STB); bulk_g2s(sb + SM_REM, G->ht + (size_t)cta * STB, STB, bbar); }
        }
        __syncwarp();
        if (cta < NKV) {
          mbar_wait(bbar, 1);
#pragma unroll 1
          for (int gi = 0; gi < 10; gi++) {
            uint4 v[4];
#pragma unroll
            for (int u = 0; u < 4; u++) { const int rr = (w - 1) * 4 + u; v[u] = lds128(sb + SM_REM + gi * 4096 + (lane >> 3) * 1024 + rr * 128 + (((lane ^ rr) & 7) << 4)); }
            bar_sync(5, 64);
#pragma unroll
            for (int u = 0; u < 4; u++) sts128(sb + SM_REM + gi * 4096 + ((w - 1) * 4 + u) * 512 + lane * 16, v[u].x, v[u].y, v[u].z, v[u].w);
          }
          PROXY_FENCE_SMEM();
          bar_sync(5, 64);
        }
        STAMPIF(threadIdx.x == 288, 44);
        mbar_wait(go, 0);
        if (lane == 0) gwait(&G->ctr[C_M], ep * CNT_M);
        __syncwarp();
        STAMPIF(threadIdx.x == 288, 4);
        if (cta < NKV) {
          const unsigned* bp = (unsigned*)at(G->box, ((w - 1) * NKV + cta) * 128 + lane * 4);
          unsigned e = __ldcg(bp);
#pragma unroll 1
          for (int i = 0; i < NCTA / 2; i++) {
            bp += 2 * NKV * 32;
            unsigned en = 0;
            if (i + 1 < NCTA / 2) en = __ldcg(bp);
            if (e) bulk_red(G->acc + (size_t)(e & 0x3fff) * 512, sb + SM_REM + ((e >> 14) & 127) * 512, 512);
            BULK_COMMIT();
            BULK_WAIT_READ();
            e = en;
          }
        }
#pragma unroll 1
        for (int i = w - 1; i < novf; i += 2) {
          const int e = __ldcg(&G->ovf[cta * 1280 + i]), r = e >> 14;
          const uint4 v = ldg_cg(G->ht + (size_t)(r >> 3) * 4096 + (lane >> 3) * 1024 + (r & 7) * 128 + (((lane ^ r) & 7) << 4));
          asm volatile("red.global.add.noftz.v4.bf16x2 [%0], {%1,%2,%3,%4};" ::"l"(G->acc + (size_t)(e & 0x3fff) * 512 + lane * 16), "r"(v.x), "r"(v.y), "r"(v.z), "r"(v.w) : "memory");
        }
        BULK_WAIT();
        __syncwarp();
        if (lane == 0) garrive(&G->ctr[C_G]);
        STAMPIF(threadIdx.x == 288, 5);
      }
    }
  } else {
    const int g = lane >> 2, t = lane & 3, wp = __shfl_sync(~0u, (threadIdx.x >> 5) & 3, 0), tid = threadIdx.x & 127;
    const uint32_t qh = sb + SM_Q + wg * 32768;
    const uint32_t qw = qh + wp * 8192;
    const uint32_t qbar = qbar0 + 8 * wg;
    auto event = [&](int e) { mbar_arrive(evt0 + 16 * e + 8 * wg); };
    if (wg == 1) bar_arrive(1, 256);
    {
      const int xr0 = min(q0 * 128 + wg * 64 + wp * 16, N_ - 16), xord = (owner || !early ? wg : wg ^ 1) * 4 + wp;
      if (cta >= 64 && xord >= 4) mbar_wait(xbar0 + 8 * (xord - 4), 0);
      if (lane == 0 && xord >= xfirst) {
        mbar_expect_tx(xbar0 + 8 * xord, 8192);
        bulk_g2s(qw, x + (size_t)xr0 * 256, 8192, xbar0 + 8 * xord);
      }
      STAMPIF(threadIdx.x == 0, 35);
      mbar_wait(xbar0 + 8 * xord, 0);
      STAMPIF(threadIdx.x == 0, 25);
      STAMPIF(threadIdx.x == 224, 41);
      uint4 xa[8], xb[8];
      const uint32_t sw = (g & 1) << 6;
#pragma unroll
      for (int J = 0; J < 8; J++) xa[J] = lds128(qw + g * 512 + t * 16 + ((J * 64) ^ sw));
#pragma unroll
      for (int J = 0; J < 8; J++) xb[J] = lds128(qw + 4096 + g * 512 + t * 16 + ((J * 64) ^ sw));
      __syncwarp();
      const uint32_t wa = qw + g * 128 + (((t ^ g) << 4) ^ sw);
#pragma unroll
      for (int rr = 0; rr < 2; rr++) {
        float sm[2][4] = {}, f[64], q[4] = {};
#pragma unroll
        for (int J = 0; J < 8; J++) {
          const uint4 v = rr ? xb[J] : xa[J];
          mma16816(sm[J & 1], v.x, v.y, v.z, v.w, 0x3f803f80u, 0x3f803f80u);
#pragma unroll
          for (int i = 0; i < 4; i++) {
            f[J * 8 + 2 * i] = blo(comp(v, i)); f[J * 8 + 2 * i + 1] = bhi(comp(v, i));
            q[i] = fmaf(f[J * 8 + 2 * i], f[J * 8 + 2 * i], q[i]); q[i ^ 2] = fmaf(f[J * 8 + 2 * i + 1], f[J * 8 + 2 * i + 1], q[i ^ 2]);
          }
        }
        const float mean = ((sm[0][0] + sm[0][2]) + (sm[1][0] + sm[1][2])) * (1.f / 256.f);
        float rstd = rsq(fmaxf(fmaf(-mean, mean, quad_sum((q[0] + q[1]) + (q[2] + q[3])) * (1.f / 256.f)), 0.f) + 1e-5f);
        if (q0 * 8 + wg * 4 + wp >= N_ / 16) rstd = 0.f;
#pragma unroll
        for (int J = 0; J < 8; J++) {
          const bool lastc = J >= 6 && (lane & 7) == (J == 7 ? 3 : 7);
          const float c = (lastc ? f[J * 8 + 7] : mean) * -rstd;
          uint32_t r3 = pack2(fmaf(f[J * 8 + 6], rstd, c), fmaf(f[J * 8 + 7], rstd, c));
          if (lastc) r3 = (r3 & 0xffffu) | 0x3f800000u;
          sts128((wa ^ ((J & 1) << 6)) + rr * 4096 + (J >> 1) * 1024, pack2(fmaf(f[J * 8], rstd, c), fmaf(f[J * 8 + 1], rstd, c)),
                 pack2(fmaf(f[J * 8 + 2], rstd, c), fmaf(f[J * 8 + 3], rstd, c)), pack2(fmaf(f[J * 8 + 4], rstd, c), fmaf(f[J * 8 + 5], rstd, c)), r3);
        }
      }
      STAMPIF(threadIdx.x == 0, 38);
      PROXY_FENCE_SMEM();
      STAMPIF(threadIdx.x == 0, 39);
    }
    event(4);
    bar_sync(3 + wg, 128);
    STAMPIF(tid == 0, wg ? 42 : 6);
    asm volatile("setmaxnreg.inc.sync.aligned.u32 224;\n");

    float o[128];
    uint32_t ga[64], qr[NQR * 4];
    uint32_t st = 0, ph = 0, pst = 0;
    const uint32_t qd = mkdesc(qh, 16), kd0 = mkdesc(ring, 16), vd0 = mkdesc(ring, 1024), rd = mkdesc(sb + SM_REM, 1024);
    auto wait_full = [&]() { mbar_wait(full0 + 8 * st, ph); };
    auto advance = [&]() { pst = st; if (++st == NST) { st = 0; ph ^= 1; } };
    auto release = [&]() { if (lane == 0) mbar_arrive(empty0 + 8 * pst); };

    {
      mbar_wait(wfirst, 0);
      bar_sync(1 + wg, 256);
      STAMPIF(threadIdx.x == 0, 28);
      WG_FENCE();
      wgmma_ss256(o, qd, vd0, 0);
      wgmma_ss256(o, qd + 2, vd0 + 512, 1);
#pragma unroll
      for (int c = 0; c < 3; c++) {
        wait_full();
        WG_FENCE();
#pragma unroll
        for (int k = c ? 0 : 2; k < 5; k++) {
          const int ks = c * 5 + k;
          wgmma_ss256(o, qd + (ks >> 2) * 64 + (ks & 3) * 2, vd0 + c * (STB >> 4) + k * 512, 1);
          if (c > 0 && k == EREL) { WG_COMMIT(); WG_WAIT(1); release(); }
        }
        if (c == 2) wgmma_ss256(o, qd + 3 * 64 + 6, rd, 1);
        WG_COMMIT();
        if (c == 2) bar_arrive(2 - wg, 256);
        advance();
      }
      WG_WAIT(0);
      pin(o);
      release();
      STAMPIF(threadIdx.x == 0, 29);
      mbar_wait(hread0 + 8 * wg, 0);
      bar_sync(3 + wg, 128);
      STAMPIF(threadIdx.x == 0, 45);
      const uint32_t sa = qw + ((lane >> 3) & 1) * 4096 + (lane & 7) * 128 + (((lane >> 4) ^ (lane & 7)) << 4);
#pragma unroll
      for (int i = 0; i < 32; i += 2)
        stsm4((sa ^ ((i & 7) << 4)) + (i >> 3) * 1024, pack2(o[4 * i], o[4 * i + 1]), pack2(o[4 * i + 2], o[4 * i + 3]), pack2(o[4 * i + 4], o[4 * i + 5]), pack2(o[4 * i + 6], o[4 * i + 7]));
#pragma unroll
      for (int i = 0; i < NQR * 4; i++) qr[i] = pack2(o[128 - NQR * 8 + 2 * i], o[129 - NQR * 8 + 2 * i]);
      STAMPIF(threadIdx.x == 0, 46);
      PROXY_FENCE_SMEM();
      event(0);
    }
    STAMPIF(threadIdx.x == 0, 7);

    float s[BN / 2];
    uint32_t p[BN / 4];
    float m0, m1, mb0, mb1, l0, l1;
    auto qk = [&]() {
#pragma unroll
      for (int ks = 0; ks < 16; ks++) {
        const uint32_t off = (ks >> 2) * 64 + (ks & 3) * 2;
        const int r = (ks - 16 + NQR) * 4;
        const uint64_t q64 = (uint64_t)DESC_HI << 32 | qd, k64 = ((uint64_t)DESC_HI << 32 | kd0) + st * (STB >> 4);
        if (r < 0) wgmma_qk64(s, q64 + off, k64 + off, ks > 0);
        else wgmma_qkr64(s, qr[r], qr[r + 1], qr[r + 2], qr[r + 3], k64 + off, 1);
      }
      WG_COMMIT();
    };
    auto pv = [&](int keep) {
#pragma unroll
      for (int ks = 0; ks < BN / 16; ks++) wgmma_pv64(o, p[ks * 4], p[ks * 4 + 1], p[ks * 4 + 2], p[ks * 4 + 3], ((uint64_t)DESC_HI << 32 | vd0) + pst * (STB >> 4) + ks * 512, ks ? 1 : keep);
      WG_COMMIT();
    };
    auto softmax_slow = [&](bool dump, bool first) {
      const float om0 = m0, om1 = m1;
      if (dump) {
        m0 = m1 = -INFINITY;
        mb0 = mb1 = 0.f;
        if (staged) {
#pragma unroll
          for (int k = 0; k < 10; k++)
            sts128(sb + SM_REM + wg * 20480 + k * 2048 + tid * 16, pack2(o[8 * k], o[8 * k + 1]), pack2(o[8 * k + 2], o[8 * k + 3]), pack2(o[8 * k + 4], o[8 * k + 5]), pack2(o[8 * k + 6], o[8 * k + 7]));
          PROXY_FENCE_SMEM();
        }
      }
      float x0 = fmaxf(s[0], s[1]), x1 = fmaxf(s[2], s[3]);
#pragma unroll
      for (int i = 1; i < BN / 8; i++) { x0 = fmaxf(x0, fmaxf(s[4 * i], s[4 * i + 1])); x1 = fmaxf(x1, fmaxf(s[4 * i + 2], s[4 * i + 3])); }
      x0 = quad_max(x0) + mb0; x1 = quad_max(x1) + mb1;
      float r0 = x0 < m0 ? m0 : ceilf(x0 + 32.f), r1 = x1 < m1 ? m1 : ceilf(x1 + 32.f);
      uint32_t pk = pack2(r0, r1);
      const float b0 = blo(pk), b1 = bhi(pk);
      const bool ok0 = fabsf(b0 - r0) <= 8.f, ok1 = fabsf(b1 - r1) <= 8.f;
      if (ok0) r0 = b0;
      if (ok1) r1 = b1;
      const float a0 = ex2(m0 - r0), a1 = ex2(m1 - r1), d0 = r0 - mb0, d1 = r1 - mb1;
      m0 = r0; m1 = r1;
      mb0 = b0; mb1 = b1;
      if (t == 3) {
        pk ^= 0x80008000u;
        qr[NQR * 4 - 2] = __byte_perm(qr[NQR * 4 - 2], pk, 0x5410);
        qr[NQR * 4 - 1] = __byte_perm(qr[NQR * 4 - 1], pk, 0x7610);
      }
      if (dump) {
        if (t == 3) {
          float2* mp = (float2*)at(G->meta, (o0 * 128 + wg * 64 + wp * 16 + g) * 8);
          mp[0] = make_float2(om0, o[125]);
          mp[8] = make_float2(om1, o[127]);
        }
        uint8_t* pp = at(G->part, o0 * 65536 + wg * 32768 + tid * 16);
#pragma unroll
        for (int k = 15; k >= 0; k--) {
          if (k == 9 && staged) break;
          stg128(pp + k * 2048, pack2(o[8 * k], o[8 * k + 1]), pack2(o[8 * k + 2], o[8 * k + 3]), pack2(o[8 * k + 4], o[8 * k + 5]), pack2(o[8 * k + 6], o[8 * k + 7]));
        }
        event(2);
        STAMPIF(tid == 0, 14 + wg);
      }
      if (!first && __any_sync(~0u, a0 != 1.f || a1 != 1.f)) {
#pragma unroll
        for (int i = 0; i < 32; i++) { o[4 * i] *= a0; o[4 * i + 1] *= a0; o[4 * i + 2] *= a1; o[4 * i + 3] *= a1; }
      }
#pragma unroll
      for (int i = 0; i < BN / 8; i++) {
        p[2 * i] = pack2(ex2(s[4 * i] - d0), ex2(s[4 * i + 1] - d0));
        p[2 * i + 1] = pack2(ex2(s[4 * i + 2] - d1), ex2(s[4 * i + 3] - d1));
      }
      return (bool)__any_sync(~0u, !(ok0 && ok1));
    };
    {
      int left = n0 + n1 - 1;
      if (cta >= 130 && wg) {
#pragma unroll 1
        for (; left > 1; left--) {
          wait_full();
          bar_sync(2, 256);
          bar_arrive(1, 256);
          advance();
          release();
        }
      }
      wait_full();
      bar_sync(1 + wg, 256);
      WG_FENCE();
      qk();
      bar_arrive(2 - wg, 256);
      m0 = m1 = -INFINITY;
      mb0 = mb1 = 0.f;
      WG_WAIT(0);
      pin(s);
      GSTAMPIF(threadIdx.x == 0, 8);
      STAMPIF(threadIdx.x == 128, 53);
      bool slow = softmax_slow(false, true);
      STAMPIF(tid == 0, 32 + wg);
      int keep = 0;
      advance();
#pragma unroll 1
      do {
        const bool sw = left == n1;
        wait_full();
        bar_sync(1 + wg, 256);
        WG_FENCE();
        pv(keep);
        keep = !sw;
        if (sw) {
          mbar_wait(qbar, 1);
          slow = true;
#pragma unroll
          for (int i = 0; i < NQR; i++) {
            const int ks = 16 - NQR + i;
            uint32_t f[4];
            ldsm4(f, qw + ((lane >> 3) & 1) * 4096 + (ks >> 2) * 1024 + (lane & 7) * 128 + ((((ks & 3) * 2 + (lane >> 4)) ^ (lane & 7)) << 4));
            qr[4 * i] = f[0]; qr[4 * i + 1] = f[1]; qr[4 * i + 2] = f[2]; qr[4 * i + 3] = f[3];
          }
        }
        WG_FENCE();
        qk();
        bar_arrive(2 - wg, 256);
        WG_WAIT(1);
        release();
        WG_WAIT(0);
        pin(s); pin(o);
        left--;
        if (left == n1 || left == 0) event(left == n1 ? 1 : 6);
        if (!slow) {
          uint32_t acc = 0;
#pragma unroll
          for (int i = 0; i < BN / 4; i++) { p[i] = pack2(ex2(s[2 * i]), ex2(s[2 * i + 1])); acc |= p[i]; }
          slow = __any_sync(~0u, (acc & 0x40004000u) != 0);
        }
        if (slow) {
          GSTAMPIF(threadIdx.x == 0 && sw, 9);
          slow = softmax_slow(sw, sw);
        }
        advance();
      } while (left);
      bar_sync(1 + wg, 256);
      WG_FENCE();
      pv(1);
      bar_arrive(2 - wg, 256);
      WG_WAIT(0);
      pin(o);
      release();
      GSTAMPIF(tid == 0, 10 + wg);
      if (i1 >= 0) {
        mbar_wait(qbar, n1 ? 0 : 1);
        STAMPIF(tid == 0, 18 + wg);
        const uint32_t ma = sb + SM_META + wg * 512 + (wp * 16 + g) * 8;
        float2 h0, h1;
        asm volatile("ld.shared.v2.f32 {%0,%1}, [%2];" : "=f"(h0.x), "=f"(h0.y) : "r"(ma) : "memory");
        asm volatile("ld.shared.v2.f32 {%0,%1}, [%2];" : "=f"(h1.x), "=f"(h1.y) : "r"(ma + 64) : "memory");
#pragma unroll
        for (int k = 0; k < 16; k++) { const uint4 v = lds128(qh + k * 2048 + tid * 16); ga[4 * k] = v.x; ga[4 * k + 1] = v.y; ga[4 * k + 2] = v.z; ga[4 * k + 3] = v.w; }
        if (__any_sync(~0u, h0.x - m0 > 20.f || h1.x - m1 > 20.f)) {
          const float t0 = fmaxf(m0, h0.x), t1 = fmaxf(m1, h1.x), a0 = ex2(m0 - t0), a1 = ex2(m1 - t1);
          m0 = t0; m1 = t1;
#pragma unroll
          for (int i = 0; i < 32; i++) { o[4 * i] *= a0; o[4 * i + 1] *= a0; o[4 * i + 2] *= a1; o[4 * i + 3] *= a1; }
        }
        const float b0 = ex2(h0.x - m0), b1 = ex2(h1.x - m1);
        l0 = fmaf(b0, h0.y, o[125]); l1 = fmaf(b1, h1.y, o[127]);
        const uint32_t bb0 = pack2(b0, b0), bb1 = pack2(b1, b1);
#pragma unroll
        for (int i = 0; i < 64; i++) ga[i] = hfma2(ga[i], (i & 1) ? bb1 : bb0, pack2(o[2 * i], o[2 * i + 1]));
      } else {
        l0 = o[125]; l1 = o[127];
#pragma unroll
        for (int i = 0; i < 64; i++) ga[i] = pack2(o[2 * i], o[2 * i + 1]);
      }
      if (!owner) {
        if (wg) mbar_wait(wsent, 1);
        const int slot = n1 ? q1 : o0;
        uint8_t* pp = at(G->part, slot * 65536 + wg * 32768 + tid * 16);
#pragma unroll
        for (int k = 0; k < 16; k++) stg128(pp + k * 2048, ga[4 * k], ga[4 * k + 1], ga[4 * k + 2], ga[4 * k + 3]);
        if (t == 3) {
          float2* mp = (float2*)at(G->meta, (slot * 128 + wg * 64 + wp * 16 + g) * 8);
          mp[0] = make_float2(m0, l0);
          mp[8] = make_float2(m1, l1);
        }
        event(3);
        STAMPIF(tid == 0, 16 + wg);
      }
    }

    float f0 = rcp(__shfl_sync(~0u, l0, lane | 3)), f1 = rcp(__shfl_sync(~0u, l1, lane | 3));
#pragma unroll 1
    for (int rnd = 0;; rnd++) {
      int r0 = q0 * 128 + wg * 64;
      if (!owner) {
        r0 = (rnd ? lu2 : lu + wg) * 64;
        mbar_wait(xbar0 + 8 * (rnd * 2 + wg), 1);
        const uint32_t la = (rnd || role == 4 ? sb + SM_AUX + wp * 8192 : qw) + g * 512 + t * 16;
#pragma unroll
        for (int J = 0; J < 8; J++) {
          const uint4 va = lds128(la + J * 64), vb = lds128(la + 4096 + J * 64);
          ga[8 * J] = va.x; ga[8 * J + 1] = vb.x; ga[8 * J + 2] = va.y; ga[8 * J + 3] = vb.y;
          ga[8 * J + 4] = va.z; ga[8 * J + 5] = vb.z; ga[8 * J + 6] = va.w; ga[8 * J + 7] = vb.w;
        }
        uint32_t d0, d1;
        asm volatile("ld.shared.u16 %0, [%1];" : "=r"(d0) : "r"(sb + SM_DINV + (rnd * 128 + wg * 64 + wp * 16 + g) * 2) : "memory");
        asm volatile("ld.shared.u16 %0, [%1];" : "=r"(d1) : "r"(sb + SM_DINV + (rnd * 128 + wg * 64 + wp * 16 + g + 8) * 2) : "memory");
        f0 = blo(d0); f1 = blo(d1);
        if (rnd == 0) event(5);
      }
      r0 += wp * 16;
#pragma unroll
      for (int i = 0; i < 64; i++) asm volatile("" : "+r"(ga[i])::"memory");
      STAMPIF(tid == 0, 47 + wg);
      bar_sync(1 + wg, 256);
#pragma unroll
      for (int c = 0; c < 3; c++) {
        if (rnd == 0) wait_full();
        WG_FENCE();
        const uint32_t wd = vd0 + st * (STB >> 4);
#pragma unroll
        for (int k = 0; k < 5; k++) { const int ks = c * 5 + k; wgmma_rs256(o, ga[ks * 4], ga[ks * 4 + 1], ga[ks * 4 + 2], ga[ks * 4 + 3], wd + k * 512, ks != 0); }
        if (c == 2) wgmma_rs256(o, ga[60], ga[61], ga[62], ga[63], rd, 1);
        WG_COMMIT();
        advance();
      }
      if (wg == 0 ? rnd == 0 : n1 != 0) bar_arrive(2 - wg, 256);
      BULK_WAIT_READ();
      __syncwarp();
      WG_WAIT(0);
      pin(o);
      STAMPIF(tid == 0, 20 + wg);
      const uint32_t ap = qw + g * 512 + t * 16 + ((g & 1) << 6);
      const bool odd = g & 1;
#pragma unroll
      for (int h = 0; h < 2; h++) {
        const float f = h ? f1 : f0;
#pragma unroll
        for (int J = 0; J < 8; J += 2) {
          uint32_t y[8];
#pragma unroll
          for (int i = 0; i < 8; i++) y[i] = pack2(o[16 * J + 4 * i + 2 * h] * f, o[16 * J + 4 * i + 2 * h + 1] * f);
          sts128(ap + h * 4096 + J * 64, odd ? y[4] : y[0], odd ? y[5] : y[1], odd ? y[6] : y[2], odd ? y[7] : y[3]);
          sts128((ap ^ 64) + h * 4096 + J * 64, odd ? y[0] : y[4], odd ? y[1] : y[5], odd ? y[2] : y[6], odd ? y[3] : y[7]);
        }
        PROXY_FENCE_SMEM();
        __syncwarp();
        if (lane == 0 && r0 < N_) { bulk_red((uint8_t*)out + (size_t)r0 * 512 + h * 4096, qw + h * 4096, 4096); BULK_COMMIT(); }
      }
      STAMPIF(tid == 0, 51 + wg);
      if (rnd || wg || !n1) break;
    }
    BULK_WAIT_READ();
    GSTAMPIF(tid == 0, 22 + wg);
    PROF_DUMP();
  }
}

}

extern "C" void kernel_launch(void* const* d_in, const int* in_sizes, int n_in, void* d_out, int out_size) {
  (void)in_sizes; (void)n_in; (void)out_size;
  void* scratch = nullptr;
  cudaGetSymbolAddress(&scratch, g_scratch);
  cudaFuncSetAttribute(gps_kernel, cudaFuncAttributeMaxDynamicSharedMemorySize, SM_TOTAL);
  gps_kernel<<<NCTA, 384, SM_TOTAL>>>((const __nv_bfloat16*)d_in[0], (const int*)d_in[1], (const int*)d_in[2],
                                      (const __nv_bfloat16*)d_in[3], (const __nv_bfloat16*)d_in[4], (const __nv_bfloat16*)d_in[5],
                                      (const __nv_bfloat16*)d_in[6], (const __nv_bfloat16*)d_in[7], (const __nv_bfloat16*)d_in[8],
                                      (__nv_bfloat16*)d_out, (Scratch*)scratch);
}
```

```cpp
#include <cuda.h>
#include <cuda_runtime.h>
#include <cuda_bf16.h>
#include <stdint.h>

namespace {

constexpr int N_ = 10000, E_ = 160000, NQT = 79, NPAD = NQT * 128;
constexpr int BN = 80, NKV = 125, NST = 3, STB = BN * 512, NCTA = 132;
constexpr int NSLOT = NQT + 26;
constexpr int SCHED_A = 76, SCHED_B = 76, SCHED_C = 76;
constexpr int SCHED_B1 = 25;
constexpr int JBG = 5, JSCAT = 49;
constexpr float OFFS = 64.f;
constexpr int B0 = 2, B1 = 16;
constexpr float BETA = 128.f;
constexpr int SM_Q = 0, SM_RING = 65536, SM_REM = SM_RING + NST * STB, SM_AUX = SM_REM + 8192, SM_META = SM_AUX + 32768;
constexpr int SM_BAR = SM_META + 1024, SM_DINV = SM_BAR + 1280, SM_TOTAL = SM_BAR + 1792;
constexpr unsigned CNT_W = 64, CNT_H = NCTA, CNT_E = 5, CNT_F = 4, CNT_M = NCTA + 64, CNT_G = NCTA * 2;
constexpr int C_W = 0, C_H = 32, C_E = 64, C_M = 96, C_G = 128, C_F = 160;

struct Scratch {
  unsigned ctr[6 * 32], epoch, pad0[31], pflag[NSLOT * 2], pad1[1024 - 7 * 32 - NSLOT * 2];
  uint8_t w[3 * 131072];
  float2 meta[NSLOT * 128];
  uint8_t ht[NPAD * 512];
  uint8_t qt[NPAD * 512];
  uint8_t acc[NCTA * 40960];
  uint8_t part[NSLOT * 65536];
  unsigned box[NCTA * NKV * 32];
  int ovf[NCTA * 1280];
};
__device__ __align__(1024) Scratch g_scratch;

constexpr uint32_t DESC_HI = 0x40000100u;
__device__ __forceinline__ void wgmma_qk64(float (&d)[40], uint64_t da, uint64_t db, int sd) {
  asm volatile("{\n.reg .pred p;\nsetp.ne.b32 p, %42, 0;\n"
    "wgmma.mma_async.sync.aligned.m64n80k16.f32.bf16.bf16 {%0, %1, %2, %3, %4, %5, %6, %7, %8, %9, %10, %11, %12, %13, %14, %15, %16, %17, %18, %19, %20, %21, %22, %23, %24, %25, %26, %27, %28, %29, %30, %31, %32, %33, %34, %35, %36, %37, %38, %39}, %40, %41, p, 1, 1, 0, 0;\n}\n"
    : "+f"(d[0]), "+f"(d[1]), "+f"(d[2]), "+f"(d[3]), "+f"(d[4]), "+f"(d[5]), "+f"(d[6]), "+f"(d[7]), "+f"(d[8]), "+f"(d[9]), "+f"(d[10]), "+f"(d[11]), "+f"(d[12]), "+f"(d[13]), "+f"(d[14]), "+f"(d[15]), "+f"(d[16]), "+f"(d[17]), "+f"(d[18]), "+f"(d[19]), "+f"(d[20]), "+f"(d[21]), "+f"(d[22]), "+f"(d[23]), "+f"(d[24]), "+f"(d[25]), "+f"(d[26]), "+f"(d[27]), "+f"(d[28]), "+f"(d[29]), "+f"(d[30]), "+f"(d[31]), "+f"(d[32]), "+f"(d[33]), "+f"(d[34]), "+f"(d[35]), "+f"(d[36]), "+f"(d[37]), "+f"(d[38]), "+f"(d[39])
    : "l"(da), "l"(db), "r"(sd));
}

__device__ __forceinline__ void wgmma_qkr64(float (&d)[40], uint32_t a0, uint32_t a1, uint32_t a2, uint32_t a3, uint64_t db, int sd) {
  asm volatile("{\n.reg .pred p;\nsetp.ne.b32 p, %45, 0;\n"
    "wgmma.mma_async.sync.aligned.m64n80k16.f32.bf16.bf16 {%0, %1, %2, %3, %4, %5, %6, %7, %8, %9, %10, %11, %12, %13, %14, %15, %16, %17, %18, %19, %20, %21, %22, %23, %24, %25, %26, %27, %28, %29, %30, %31, %32, %33, %34, %35, %36, %37, %38, %39}, {%40, %41, %42, %43}, %44, p, 1, 1, 0;\n}\n"
    : "+f"(d[0]), "+f"(d[1]), "+f"(d[2]), "+f"(d[3]), "+f"(d[4]), "+f"(d[5]), "+f"(d[6]), "+f"(d[7]), "+f"(d[8]), "+f"(d[9]), "+f"(d[10]), "+f"(d[11]), "+f"(d[12]), "+f"(d[13]), "+f"(d[14]), "+f"(d[15]), "+f"(d[16]), "+f"(d[17]), "+f"(d[18]), "+f"(d[19]), "+f"(d[20]), "+f"(d[21]), "+f"(d[22]), "+f"(d[23]), "+f"(d[24]), "+f"(d[25]), "+f"(d[26]), "+f"(d[27]), "+f"(d[28]), "+f"(d[29]), "+f"(d[30]), "+f"(d[31]), "+f"(d[32]), "+f"(d[33]), "+f"(d[34]), "+f"(d[35]), "+f"(d[36]), "+f"(d[37]), "+f"(d[38]), "+f"(d[39])
    : "r"(a0), "r"(a1), "r"(a2), "r"(a3), "l"(db), "r"(sd));
}

__device__ __forceinline__ void wgmma_pv64(float (&d)[128], uint32_t a0, uint32_t a1, uint32_t a2, uint32_t a3, uint64_t db, int sd) {
  asm volatile("{\n.reg .pred p;\nsetp.ne.b32 p, %133, 0;\n"
    "wgmma.mma_async.sync.aligned.m64n256k16.f32.bf16.bf16 {%0, %1, %2, %3, %4, %5, %6, %7, %8, %9, %10, %11, %12, %13, %14, %15, %16, %17, %18, %19, %20, %21, %22, %23, %24, %25, %26, %27, %28, %29, %30, %31, %32, %33, %34, %35, %36, %37, %38, %39, %40, %41, %42, %43, %44, %45, %46, %47, %48, %49, %50, %51, %52, %53, %54, %55, %56, %57, %58, %59, %60, %61, %62, %63, %64, %65, %66, %67, %68, %69, %70, %71, %72, %73, %74, %75, %76, %77, %78, %79, %80, %81, %82, %83, %84, %85, %86, %87, %88, %89, %90, %91, %92, %93, %94, %95, %96, %97, %98, %99, %100, %101, %102, %103, %104, %105, %106, %107, %108, %109, %110, %111, %112, %113, %114, %115, %116, %117, %118, %119, %120, %121, %122, %123, %124, %125, %126, %127}, {%128, %129, %130, %131}, %132, p, 1, 1, 1;\n}\n"
    : "+f"(d[0]), "+f"(d[1]), "+f"(d[2]), "+f"(d[3]), "+f"(d[4]), "+f"(d[5]), "+f"(d[6]), "+f"(d[7]), "+f"(d[8]), "+f"(d[9]), "+f"(d[10]), "+f"(d[11]), "+f"(d[12]), "+f"(d[13]), "+f"(d[14]), "+f"(d[15]), "+f"(d[16]), "+f"(d[17]), "+f"(d[18]), "+f"(d[19]), "+f"(d[20]), "+f"(d[21]), "+f"(d[22]), "+f"(d[23]), "+f"(d[24]), "+f"(d[25]), "+f"(d[26]), "+f"(d[27]), "+f"(d[28]), "+f"(d[29]), "+f"(d[30]), "+f"(d[31]), "+f"(d[32]), "+f"(d[33]), "+f"(d[34]), "+f"(d[35]), "+f"(d[36]), "+f"(d[37]), "+f"(d[38]), "+f"(d[39]), "+f"(d[40]), "+f"(d[41]), "+f"(d[42]), "+f"(d[43]), "+f"(d[44]), "+f"(d[45]), "+f"(d[46]), "+f"(d[47]), "+f"(d[48]), "+f"(d[49]), "+f"(d[50]), "+f"(d[51]), "+f"(d[52]), "+f"(d[53]), "+f"(d[54]), "+f"(d[55]), "+f"(d[56]), "+f"(d[57]), "+f"(d[58]), "+f"(d[59]), "+f"(d[60]), "+f"(d[61]), "+f"(d[62]), "+f"(d[63]), "+f"(d[64]), "+f"(d[65]), "+f"(d[66]), "+f"(d[67]), "+f"(d[68]), "+f"(d[69]), "+f"(d[70]), "+f"(d[71]), "+f"(d[72]), "+f"(d[73]), "+f"(d[74]), "+f"(d[75]), "+f"(d[76]), "+f"(d[77]), "+f"(d[78]), "+f"(d[79]), "+f"(d[80]), "+f"(d[81]), "+f"(d[82]), "+f"(d[83]), "+f"(d[84]), "+f"(d[85]), "+f"(d[86]), "+f"(d[87]), "+f"(d[88]), "+f"(d[89]), "+f"(d[90]), "+f"(d[91]), "+f"(d[92]), "+f"(d[93]), "+f"(d[94]), "+f"(d[95]), "+f"(d[96]), "+f"(d[97]), "+f"(d[98]), "+f"(d[99]), "+f"(d[100]), "+f"(d[101]), "+f"(d[102]), "+f"(d[103]), "+f"(d[104]), "+f"(d[105]), "+f"(d[106]), "+f"(d[107]), "+f"(d[108]), "+f"(d[109]), "+f"(d[110]), "+f"(d[111]), "+f"(d[112]), "+f"(d[113]), "+f"(d[114]), "+f"(d[115]), "+f"(d[116]), "+f"(d[117]), "+f"(d[118]), "+f"(d[119]), "+f"(d[120]), "+f"(d[121]), "+f"(d[122]), "+f"(d[123]), "+f"(d[124]), "+f"(d[125]), "+f"(d[126]), "+f"(d[127])
    : "r"(a0), "r"(a1), "r"(a2), "r"(a3), "l"(db), "r"(sd));
}

__device__ __forceinline__ void wgmma_ss256(float (&d)[128], uint32_t da, uint32_t db, int sd) {
  asm volatile("{\n.reg .pred p;\n.reg .b64 da, db;\nmov.b64 da, {%128, %131};\nmov.b64 db, {%129, %131};\nsetp.ne.b32 p, %130, 0;\n"
    "wgmma.mma_async.sync.aligned.m64n256k16.f32.bf16.bf16 {%0, %1, %2, %3, %4, %5, %6, %7, %8, %9, %10, %11, %12, %13, %14, %15, %16, %17, %18, %19, %20, %21, %22, %23, %24, %25, %26, %27, %28, %29, %30, %31, %32, %33, %34, %35, %36, %37, %38, %39, %40, %41, %42, %43, %44, %45, %46, %47, %48, %49, %50, %51, %52, %53, %54, %55, %56, %57, %58, %59, %60, %61, %62, %63, %64, %65, %66, %67, %68, %69, %70, %71, %72, %73, %74, %75, %76, %77, %78, %79, %80, %81, %82, %83, %84, %85, %86, %87, %88, %89, %90, %91, %92, %93, %94, %95, %96, %97, %98, %99, %100, %101, %102, %103, %104, %105, %106, %107, %108, %109, %110, %111, %112, %113, %114, %115, %116, %117, %118, %119, %120, %121, %122, %123, %124, %125, %126, %127}, da, db, p, 1, 1, 0, 1;\n}\n"
    : "+f"(d[0]), "+f"(d[1]), "+f"(d[2]), "+f"(d[3]), "+f"(d[4]), "+f"(d[5]), "+f"(d[6]), "+f"(d[7]), "+f"(d[8]), "+f"(d[9]), "+f"(d[10]), "+f"(d[11]), "+f"(d[12]), "+f"(d[13]), "+f"(d[14]), "+f"(d[15]), "+f"(d[16]), "+f"(d[17]), "+f"(d[18]), "+f"(d[19]), "+f"(d[20]), "+f"(d[21]), "+f"(d[22]), "+f"(d[23]), "+f"(d[24]), "+f"(d[25]), "+f"(d[26]), "+f"(d[27]), "+f"(d[28]), "+f"(d[29]), "+f"(d[30]), "+f"(d[31]), "+f"(d[32]), "+f"(d[33]), "+f"(d[34]), "+f"(d[35]), "+f"(d[36]), "+f"(d[37]), "+f"(d[38]), "+f"(d[39]), "+f"(d[40]), "+f"(d[41]), "+f"(d[42]), "+f"(d[43]), "+f"(d[44]), "+f"(d[45]), "+f"(d[46]), "+f"(d[47]), "+f"(d[48]), "+f"(d[49]), "+f"(d[50]), "+f"(d[51]), "+f"(d[52]), "+f"(d[53]), "+f"(d[54]), "+f"(d[55]), "+f"(d[56]), "+f"(d[57]), "+f"(d[58]), "+f"(d[59]), "+f"(d[60]), "+f"(d[61]), "+f"(d[62]), "+f"(d[63]), "+f"(d[64]), "+f"(d[65]), "+f"(d[66]), "+f"(d[67]), "+f"(d[68]), "+f"(d[69]), "+f"(d[70]), "+f"(d[71]), "+f"(d[72]), "+f"(d[73]), "+f"(d[74]), "+f"(d[75]), "+f"(d[76]), "+f"(d[77]), "+f"(d[78]), "+f"(d[79]), "+f"(d[80]), "+f"(d[81]), "+f"(d[82]), "+f"(d[83]), "+f"(d[84]), "+f"(d[85]), "+f"(d[86]), "+f"(d[87]), "+f"(d[88]), "+f"(d[89]), "+f"(d[90]), "+f"(d[91]), "+f"(d[92]), "+f"(d[93]), "+f"(d[94]), "+f"(d[95]), "+f"(d[96]), "+f"(d[97]), "+f"(d[98]), "+f"(d[99]), "+f"(d[100]), "+f"(d[101]), "+f"(d[102]), "+f"(d[103]), "+f"(d[104]), "+f"(d[105]), "+f"(d[106]), "+f"(d[107]), "+f"(d[108]), "+f"(d[109]), "+f"(d[110]), "+f"(d[111]), "+f"(d[112]), "+f"(d[113]), "+f"(d[114]), "+f"(d[115]), "+f"(d[116]), "+f"(d[117]), "+f"(d[118]), "+f"(d[119]), "+f"(d[120]), "+f"(d[121]), "+f"(d[122]), "+f"(d[123]), "+f"(d[124]), "+f"(d[125]), "+f"(d[126]), "+f"(d[127])
    : "r"(da), "r"(db), "r"(sd), "r"(DESC_HI));
}

__device__ __forceinline__ void wgmma_rs40(float (&d)[20], uint32_t a0, uint32_t a1, uint32_t a2, uint32_t a3, uint32_t db, int sd) {
  asm volatile("{\n.reg .pred p;\n.reg .b64 da, db;\nmov.b64 db, {%24, %26};\nsetp.ne.b32 p, %25, 0;\n"
    "wgmma.mma_async.sync.aligned.m64n40k16.f32.bf16.bf16 {%0, %1, %2, %3, %4, %5, %6, %7, %8, %9, %10, %11, %12, %13, %14, %15, %16, %17, %18, %19}, {%20, %21, %22, %23}, db, p, 1, 1, 0;\n}\n"
    : "+f"(d[0]), "+f"(d[1]), "+f"(d[2]), "+f"(d[3]), "+f"(d[4]), "+f"(d[5]), "+f"(d[6]), "+f"(d[7]), "+f"(d[8]), "+f"(d[9]), "+f"(d[10]), "+f"(d[11]), "+f"(d[12]), "+f"(d[13]), "+f"(d[14]), "+f"(d[15]), "+f"(d[16]), "+f"(d[17]), "+f"(d[18]), "+f"(d[19])
    : "r"(a0), "r"(a1), "r"(a2), "r"(a3), "r"(db), "r"(sd), "r"(DESC_HI));
}

__device__ __forceinline__ void wgmma_rs128(float (&d)[64], uint32_t a0, uint32_t a1, uint32_t a2, uint32_t a3, uint32_t db, int sd) {
  asm volatile("{\n.reg .pred p;\n.reg .b64 da, db;\nmov.b64 db, {%68, %70};\nsetp.ne.b32 p, %69, 0;\n"
    "wgmma.mma_async.sync.aligned.m64n128k16.f32.bf16.bf16 {%0, %1, %2, %3, %4, %5, %6, %7, %8, %9, %10, %11, %12, %13, %14, %15, %16, %17, %18, %19, %20, %21, %22, %23, %24, %25, %26, %27, %28, %29, %30, %31, %32, %33, %34, %35, %36, %37, %38, %39, %40, %41, %42, %43, %44, %45, %46, %47, %48, %49, %50, %51, %52, %53, %54, %55, %56, %57, %58, %59, %60, %61, %62, %63}, {%64, %65, %66, %67}, db, p, 1, 1, 1;\n}\n"
    : "+f"(d[0]), "+f"(d[1]), "+f"(d[2]), "+f"(d[3]), "+f"(d[4]), "+f"(d[5]), "+f"(d[6]), "+f"(d[7]), "+f"(d[8]), "+f"(d[9]), "+f"(d[10]), "+f"(d[11]), "+f"(d[12]), "+f"(d[13]), "+f"(d[14]), "+f"(d[15]), "+f"(d[16]), "+f"(d[17]), "+f"(d[18]), "+f"(d[19]), "+f"(d[20]), "+f"(d[21]), "+f"(d[22]), "+f"(d[23]), "+f"(d[24]), "+f"(d[25]), "+f"(d[26]), "+f"(d[27]), "+f"(d[28]), "+f"(d[29]), "+f"(d[30]), "+f"(d[31]), "+f"(d[32]), "+f"(d[33]), "+f"(d[34]), "+f"(d[35]), "+f"(d[36]), "+f"(d[37]), "+f"(d[38]), "+f"(d[39]), "+f"(d[40]), "+f"(d[41]), "+f"(d[42]), "+f"(d[43]), "+f"(d[44]), "+f"(d[45]), "+f"(d[46]), "+f"(d[47]), "+f"(d[48]), "+f"(d[49]), "+f"(d[50]), "+f"(d[51]), "+f"(d[52]), "+f"(d[53]), "+f"(d[54]), "+f"(d[55]), "+f"(d[56]), "+f"(d[57]), "+f"(d[58]), "+f"(d[59]), "+f"(d[60]), "+f"(d[61]), "+f"(d[62]), "+f"(d[63])
    : "r"(a0), "r"(a1), "r"(a2), "r"(a3), "r"(db), "r"(sd), "r"(DESC_HI));
}

__device__ __forceinline__ void wgmma_rs64t(float (&d)[32], uint32_t a0, uint32_t a1, uint32_t a2, uint32_t a3, uint32_t db, int sd) {
  asm volatile("{\n.reg .pred p;\n.reg .b64 da, db;\nmov.b64 db, {%36, %38};\nsetp.ne.b32 p, %37, 0;\n"
    "wgmma.mma_async.sync.aligned.m64n64k16.f32.bf16.bf16 {%0, %1, %2, %3, %4, %5, %6, %7, %8, %9, %10, %11, %12, %13, %14, %15, %16, %17, %18, %19, %20, %21, %22, %23, %24, %25, %26, %27, %28, %29, %30, %31}, {%32, %33, %34, %35}, db, p, 1, 1, 1;\n}\n"
    : "+f"(d[0]), "+f"(d[1]), "+f"(d[2]), "+f"(d[3]), "+f"(d[4]), "+f"(d[5]), "+f"(d[6]), "+f"(d[7]), "+f"(d[8]), "+f"(d[9]), "+f"(d[10]), "+f"(d[11]), "+f"(d[12]), "+f"(d[13]), "+f"(d[14]), "+f"(d[15]), "+f"(d[16]), "+f"(d[17]), "+f"(d[18]), "+f"(d[19]), "+f"(d[20]), "+f"(d[21]), "+f"(d[22]), "+f"(d[23]), "+f"(d[24]), "+f"(d[25]), "+f"(d[26]), "+f"(d[27]), "+f"(d[28]), "+f"(d[29]), "+f"(d[30]), "+f"(d[31])
    : "r"(a0), "r"(a1), "r"(a2), "r"(a3), "r"(db), "r"(sd), "r"(0x40000040u));
}


__device__ __forceinline__ uint32_t mkdesc(uint32_t addr, uint32_t lbo) { return ((addr & 0x3FFFF) >> 4) | ((lbo >> 4) << 16); }
#define WG_FENCE() asm volatile("wgmma.fence.sync.aligned;\n" ::: "memory")
#define WG_COMMIT() asm volatile("wgmma.commit_group.sync.aligned;\n" ::: "memory")
#define WG_WAIT(n) asm volatile("wgmma.wait_group.sync.aligned %0;\n" ::"n"(n) : "memory")
template <int N> __device__ __forceinline__ void pin(float (&d)[N]) {
#pragma unroll
  for (int i = 0; i < N; i++) asm volatile("" : "+f"(d[i])::"memory");
}
#define PROXY_FENCE_SMEM() asm volatile("fence.proxy.async.shared::cta;\n" ::: "memory")

__device__ __forceinline__ void mbar_init(uint32_t bar, uint32_t cnt) { asm volatile("mbarrier.init.shared::cta.b64 [%0], %1;\n" ::"r"(bar), "r"(cnt) : "memory"); }
__device__ __forceinline__ void mbar_expect_tx(uint32_t bar, uint32_t bytes) { asm volatile("mbarrier.arrive.expect_tx.shared::cta.b64 _, [%0], %1;\n" ::"r"(bar), "r"(bytes) : "memory"); }
__device__ __forceinline__ void mbar_arrive(uint32_t bar) { asm volatile("mbarrier.arrive.shared::cta.b64 _, [%0];\n" ::"r"(bar) : "memory"); }
__device__ __forceinline__ void mbar_wait(uint32_t bar, uint32_t parity) {
  asm volatile("{\n.reg .pred p;\n.reg .u32 n;\n.reg .u64 z;\nmov.u64 z, 0;\nmov.u32 n, 0;\n"
               "LAB_WAIT:\n"
               "mbarrier.try_wait.parity.shared::cta.b64 p, [%0], %1;\n"
               "@p bra LAB_DONE;\n"
               "add.u32 n, n, 1;\n"
               "setp.gt.u32 p, n, 20000000;\n"
               "@p st.global.u32 [z], n;\n"
               "bra LAB_WAIT;\n"
               "LAB_DONE:\n}\n" ::"r"(bar), "r"(parity) : "memory");
}
__device__ __forceinline__ void gwait(const unsigned* p, unsigned target) {
  asm volatile("{\n.reg .pred p;\n.reg .u32 n, v;\n.reg .u64 z;\nmov.u64 z, 0;\nmov.u32 n, 0;\n"
               "LAB_WAIT:\n"
               "ld.acquire.gpu.global.u32 v, [%0];\n"
               "sub.u32 v, v, %1;\n"
               "setp.ge.s32 p, v, 0;\n"
               "@p bra LAB_DONE;\n"
               "add.u32 n, n, 1;\n"
               "setp.gt.u32 p, n, 4000000;\n"
               "@p st.global.u32 [z], n;\n"
               "bra LAB_WAIT;\n"
               "LAB_DONE:\n}\n" ::"l"(p), "r"(target) : "memory");
}
#define GPU_FENCE() asm volatile("fence.acq_rel.gpu;\n" ::: "memory")
__device__ __forceinline__ void garrive(unsigned* p) { asm volatile("red.release.gpu.global.add.u32 [%0], 1;\n" ::"l"(p) : "memory"); }
__device__ __forceinline__ void garrive_relaxed(unsigned* p) { asm volatile("red.relaxed.gpu.global.add.u32 [%0], 1;\n" ::"l"(p) : "memory"); }
__device__ __forceinline__ void gset(unsigned* p, unsigned v) { asm volatile("st.release.gpu.global.u32 [%0], %1;\n" ::"l"(p), "r"(v) : "memory"); }
__device__ __forceinline__ void bulk_g2s(uint32_t dst, const void* src, uint32_t bytes, uint32_t bar) {
  asm volatile("cp.async.bulk.shared::cluster.global.mbarrier::complete_tx::bytes [%0], [%1], %2, [%3];\n" ::"r"(dst), "l"(src), "r"(bytes), "r"(bar) : "memory");
}
template <class T> __device__ __forceinline__ uint8_t* at(T* p, uint32_t off) {
  uint64_t r;
  asm("{\n.reg .u32 lo, hi;\nmov.b64 {lo, hi}, %1;\nadd.cc.u32 lo, lo, %2;\naddc.u32 hi, hi, 0;\nmov.b64 %0, {lo, hi};\n}" : "=l"(r) : "l"(p), "r"(off));
  return (uint8_t*)r;
}
__device__ __forceinline__ void bar_sync(int id, int n) { asm volatile("bar.sync %0, %1;\n" ::"r"(id), "r"(n) : "memory"); }
__device__ __forceinline__ void bar_arrive(int id, int n) { asm volatile("bar.arrive %0, %1;\n" ::"r"(id), "r"(n) : "memory"); }
__device__ __forceinline__ float ex2(float x) { float y; asm("ex2.approx.ftz.f32 %0, %1;" : "=f"(y) : "f"(x)); return y; }
__device__ __forceinline__ float rcp(float x) { float y; asm volatile("rcp.approx.ftz.f32 %0, %1;" : "=f"(y) : "f"(x)); return y; }
__device__ __forceinline__ float rsq(float x) { float y; asm("rsqrt.approx.ftz.f32 %0, %1;" : "=f"(y) : "f"(x)); return y; }
__device__ __forceinline__ uint32_t pack2(float lo, float hi) { uint32_t r; asm("cvt.rn.bf16x2.f32 %0, %1, %2;" : "=r"(r) : "f"(hi), "f"(lo)); return r; }
__device__ __forceinline__ float blo(uint32_t v) { return __uint_as_float(v << 16); }
__device__ __forceinline__ float bhi(uint32_t v) { return __uint_as_float(v & 0xffff0000u); }
__device__ __forceinline__ uint4 ldg_cg(const void* p) { uint4 v; asm volatile("ld.global.cg.v4.u32 {%0,%1,%2,%3}, [%4];" : "=r"(v.x), "=r"(v.y), "=r"(v.z), "=r"(v.w) : "l"(p) : "memory"); return v; }
__device__ __forceinline__ void stg128(void* p, uint32_t a, uint32_t b, uint32_t c, uint32_t d) { asm volatile("st.global.v4.u32 [%0], {%1,%2,%3,%4};" ::"l"(p), "r"(a), "r"(b), "r"(c), "r"(d) : "memory"); }
__device__ __forceinline__ void sts128(uint32_t p, uint32_t a, uint32_t b, uint32_t c, uint32_t d) { asm volatile("st.shared.v4.u32 [%0], {%1,%2,%3,%4};" ::"r"(p), "r"(a), "r"(b), "r"(c), "r"(d) : "memory"); }
__device__ __forceinline__ uint4 lds128(uint32_t p) { uint4 v; asm volatile("ld.shared.v4.u32 {%0,%1,%2,%3}, [%4];" : "=r"(v.x), "=r"(v.y), "=r"(v.z), "=r"(v.w) : "r"(p) : "memory"); return v; }
__device__ __forceinline__ float quad_sum(float v) { v += __shfl_xor_sync(~0u, v, 1); return v + __shfl_xor_sync(~0u, v, 2); }
__device__ __forceinline__ float quad_max(float v) { v = fmaxf(v, __shfl_xor_sync(~0u, v, 1)); return fmaxf(v, __shfl_xor_sync(~0u, v, 2)); }
__device__ __forceinline__ void mma16816(float (&d)[4], uint32_t a0, uint32_t a1, uint32_t a2, uint32_t a3, uint32_t b0, uint32_t b1) {
  asm("mma.sync.aligned.m16n8k16.row.col.f32.bf16.bf16.f32 {%0,%1,%2,%3}, {%4,%5,%6,%7}, {%8,%9}, {%0,%1,%2,%3};"
               : "+f"(d[0]), "+f"(d[1]), "+f"(d[2]), "+f"(d[3]) : "r"(a0), "r"(a1), "r"(a2), "r"(a3), "r"(b0), "r"(b1));
}
__device__ __forceinline__ uint32_t comp(const uint4& v, int i) { return i == 0 ? v.x : i == 1 ? v.y : i == 2 ? v.z : v.w; }
__device__ __forceinline__ void bulk_s2g(void* dst, uint32_t src, uint32_t bytes) {
  asm volatile("cp.async.bulk.global.shared::cta.bulk_group [%0], [%1], %2;\n" ::"l"(dst), "r"(src), "r"(bytes) : "memory");
}
__device__ __forceinline__ void bulk_red(void* dst, uint32_t src, uint32_t bytes) {
  asm volatile("cp.reduce.async.bulk.global.shared::cta.bulk_group.add.noftz.bf16 [%0], [%1], %2;\n" ::"l"(dst), "r"(src), "r"(bytes) : "memory");
}
#define BULK_COMMIT() asm volatile("cp.async.bulk.commit_group;\n" ::: "memory")
#define BULK_WAIT_READ() asm volatile("cp.async.bulk.wait_group.read 0;\n" ::: "memory")
#define BULK_WAIT() asm volatile("cp.async.bulk.wait_group 0;\n" ::: "memory")
__device__ __forceinline__ void cp16(uint32_t dst, const void* src) { asm volatile("cp.async.cg.shared.global [%0], [%1], 16;\n" ::"r"(dst), "l"(src) : "memory"); }
__device__ __forceinline__ void ldsm4(uint32_t (&r)[4], uint32_t p) {
  asm volatile("ldmatrix.sync.aligned.m8n8.x4.shared.b16 {%0,%1,%2,%3}, [%4];" : "=r"(r[0]), "=r"(r[1]), "=r"(r[2]), "=r"(r[3]) : "r"(p));
}
__device__ __forceinline__ void stsm4(uint32_t p, uint32_t a, uint32_t b, uint32_t c, uint32_t d) {
  asm volatile("stmatrix.sync.aligned.m8n8.x4.shared.b16 [%0], {%1,%2,%3,%4};" ::"r"(p), "r"(a), "r"(b), "r"(c), "r"(d) : "memory");
}
__device__ __forceinline__ uint32_t hfma2(uint32_t a, uint32_t b, uint32_t c) { uint32_t r; asm("fma.rn.bf16x2 %0, %1, %2, %3;" : "=r"(r) : "r"(a), "r"(b), "r"(c)); return r; }

__device__ __forceinline__ void product_load(const bool qk, const bool kperm, const __nv_bfloat16* __restrict__ L, const __nv_bfloat16* __restrict__ R,
                                             int d0, int c0, uint32_t sm) {
  const int ch = threadIdx.x & 31, w = threadIdx.x >> 5;
  const uint32_t smr = sm + 40 * 512;
  const __nv_bfloat16* lp = L + (d0 + (kperm ? ((w & 6) << 2) | (w & 1) : w)) * 256 + ch * 8;
  const uint32_t ls = sm + w * 512 + ((ch ^ w) << 4);
#pragma unroll
  for (int i = 0; i < 4; i++) cp16(ls + i * 4096, lp + i * (kperm ? 512 : 2048));
  cp16(ls + 4 * 4096, L + (248 + w) * 256 + ch * 8);
  if (qk) {
    const uint32_t rs = smr + (ch >> 3) * 1024 + w * 128 + (((ch ^ w) & 7) << 4);
#pragma unroll
    for (int i = 0; i < 4; i++) cp16(rs + i * 4096, R + (c0 + w + i * 8) * 256 + ch * 8);
    cp16(rs + 4 * 4096, R + (248 + w) * 256 + ch * 8);
  } else {
    const int e = w * 4 + (ch >> 3);
#pragma unroll
    for (int i = 0; i < 8; i++) cp16(smr + (e + i * 32) * 128 + (((ch ^ e) & 7) << 4), R + (e + i * 32) * 256 + c0 + (ch & 7) * 8);
  }
}
template <bool qk>
__device__ __forceinline__ void product_mma(uint8_t* img, int d0, int c0, uint32_t sm) {
  const int lane = threadIdx.x & 31, w = (threadIdx.x >> 5) & 3, l7 = lane & 7;
  const uint32_t pa = sm + (((lane & 8) ? 32 : w * 8) + l7) * 512;
  const uint32_t bd = mkdesc(sm + 40 * 512, 16);
  uint32_t a[16][4];
#pragma unroll
  for (int u = 0; u < 16; u++) ldsm4(a[u], pa + (u >> 2) * 128 + ((((u & 3) * 2 + (lane >> 4)) ^ l7) << 4));
  constexpr int NT = qk ? 4 : 8;
  float m[qk ? 20 : 32];
  pin(m);
  WG_FENCE();
#pragma unroll
  for (int u = 0; u < 16; u++) {
    if constexpr (qk) wgmma_rs40(m, a[u][0], a[u][1], a[u][2], a[u][3], bd + (u >> 2) * 64 + (u & 3) * 2, u);
    else wgmma_rs64t(m, a[u][0], a[u][1], a[u][2], a[u][3], bd + u * 128, u);
  }
  WG_COMMIT();
  WG_WAIT(0);
  pin(m);
  float z = 0.f, u = 0.f;
  if constexpr (qk) { z = quad_sum(m[18] + m[19]); u = quad_sum(m[16] + m[17]); }
#pragma unroll
  for (int o = 4; o < 32; o *= 2) {
#pragma unroll
    for (int n = 0; n < NT; n++) { m[4 * n + 2] += __shfl_xor_sync(~0u, m[4 * n + 2], o); m[4 * n + 3] += __shfl_xor_sync(~0u, m[4 * n + 3], o); }
    if constexpr (qk) z += __shfl_xor_sync(~0u, z, o);
  }
  const int g = lane >> 2, t = lane & 3;
  u -= z * 0.125f;
  const float sc = d0 + w * 8 + g == 255 ? 0.f : qk ? 1.4426950408889634f / 16.f : 1.f;
  uint32_t v[NT];
#pragma unroll
  for (int n = 0; n < NT; n++) v[n] = pack2(fmaf(m[4 * n + 2] + u, -0.125f, m[4 * n]) * sc, fmaf(m[4 * n + 3] + u, -0.125f, m[4 * n + 1]) * sc);
  uint8_t* gp = img + ((d0 >> 3) + w) * 4096 + (c0 >> 6) * 1024 + g * 128;
  if (qk && c0 == 224 && t == 3) v[3] &= 0xffffu;
  const uint32_t so = sm + 57344 + w * 1024;
#pragma unroll
  for (int n = 0; n < NT; n += 4) stsm4(so + l7 * 128 + (((n + (lane >> 3)) ^ l7) << 4), v[n], v[n + 1], v[n + 2], v[n + 3]);
  __syncwarp();
#pragma unroll
  for (int n = 0; n < NT; n += 4) {
    const uint4 r = lds128(so + g * 128 + (((n + t) ^ g) << 4));
    stg128(gp + (((n + t + ((c0 >> 3) & 4)) ^ g) << 4), r.x, r.y, r.z, r.w);
  }
}
__device__ __forceinline__ void product_done(unsigned* ctr) {
  bar_sync(5, 128);
  if (threadIdx.x == (blockIdx.x < 64 ? 256 : 288)) garrive(ctr);
  __syncwarp();
}

__global__ void __launch_bounds__(384, 1)
gps_kernel(const __nv_bfloat16* __restrict__ x, const int* __restrict__ src, const int* __restrict__ dst,
           const __nv_bfloat16* __restrict__ deg_inv, const __nv_bfloat16* __restrict__ w_msg,
           const __nv_bfloat16* __restrict__ wq, const __nv_bfloat16* __restrict__ wk, const __nv_bfloat16* __restrict__ wv,
           const __nv_bfloat16* __restrict__ w_out, __nv_bfloat16* __restrict__ out, Scratch* G,
           const __grid_constant__ CUtensorMap omap) {
  extern __shared__ __align__(1024) uint8_t smem_raw[];
  const uint32_t sb = (uint32_t)__cvta_generic_to_shared(smem_raw);
  const uint32_t ring = sb + SM_RING, full0 = sb + SM_BAR, empty0 = full0 + 8 * NST, qbar0 = empty0 + 8 * NST;
  const uint32_t evt0 = qbar0 + 16, one0 = evt0 + 112;
  const uint32_t sfree = one0, wsent = one0 + 8, wfirst = one0 + 16, go = one0 + 24, bbar = one0 + 32, hread0 = one0 + 40, xbar0 = one0 + 56, cbar = one0 + 120, ebar = one0 + 128, sdone = one0 + 136;
  const int wg = __shfl_sync(~0u, threadIdx.x >> 7, 0);
  const int lane = threadIdx.x & 31;
  const int cta = blockIdx.x;
  const bool prod = cta < 126 || cta >= 130;
  const int pi = cta < 126 ? cta : cta - 4;
  const int kind = max((pi >> 5) - 1, 0), pd0 = ((pi >> (kind ? 2 : 3)) & 7) * 32, pc0 = kind ? (pi & 3) * 64 : (pi & 7) * 32;
  const bool early = cta > 125 && cta < 131;
  const int xfirst = cta == 130 ? 1 : early ? 4 : 0;
  const uint32_t cnt = sb + SM_META, box = sb + SM_AUX;
  const int e0 = cta * 1216, ne = min(E_ - e0, 1216);
  if (wg < 2) {
    if (prod) product_load(kind == 0, kind == 1, kind == 0 ? wq : kind == 1 ? w_msg : wv, kind == 0 ? wk : w_out, pd0, pc0, ring);
  } else if (threadIdx.x < 320) {
#pragma unroll 1
    for (int i = threadIdx.x - 256; i < 1024 + 32; i += 64) sts128(i < 1024 ? box + i * 16 : cnt + (i - 1024) * 16, 0, 0, 0, 0);
  } else if (threadIdx.x == 352) {
    cp16(sb + SM_BAR + 496, &G->epoch);
  } else if (threadIdx.x == 320) {
#pragma unroll
    for (int i = 0; i < 40; i++) mbar_init(full0 + 8 * i, i >= 3 && i < 6 ? 8 : i >= 8 && i < 22 ? 128 : i == 37 ? 384 : i == 39 ? 2 : 1);
    asm volatile("fence.mbarrier_init.release.cluster;\n" ::: "memory");
    const int r = cta % 5, t0 = (cta / 5) * 3 + (r < 3 ? r : r - 2);
#pragma unroll 1
    for (int i = 0; i < xfirst; i++) {
      const int pc = r < 3 ? i : i ^ 4;
      mbar_expect_tx(xbar0 + 8 * i, 8192);
      bulk_g2s(sb + SM_Q + pc * 8192, x + (size_t)(t0 * 128 + pc * 16) * 256, 8192, xbar0 + 8 * i);
    }
  }

  const int grp = cta / 5, role = cta < 130 ? cta - grp * 5 : (cta == 130 ? 1 : 5);
  const bool owner = role < 3;
  const int tA = grp * 3;
  int q0, n0, o0, q1 = 0, k1 = 0, n1 = 0, i1 = -1;
  if (cta >= 130) { q0 = 78; n0 = owner ? 64 : NKV - 64; o0 = 78; if (owner) i1 = 78; }
  else if (owner) { q0 = tA + role; n0 = role == 0 ? SCHED_A : role == 1 ? SCHED_B : SCHED_C; i1 = o0 = q0; }
  else if (role == 3) { q0 = tA + 1; n0 = SCHED_B1; o0 = NQT + grp; q1 = tA; k1 = SCHED_A; n1 = NKV - SCHED_A; }
  else { q0 = tA + 2; n0 = NKV - SCHED_C; o0 = q0; q1 = tA + 1; k1 = SCHED_B; n1 = NKV - SCHED_B - SCHED_B1; i1 = NQT + grp; }
  const int lu = (role == 3 ? tA : q0) * 2, lu2 = (tA + 1) * 2 + role - 3;

  const bool staged = role == 3;

  __syncthreads();
  asm volatile("cp.async.mbarrier.arrive.noinc.shared::cta.b64 [%0];\n" ::"r"(cbar) : "memory");

  if (wg == 2) {
    mbar_wait(cbar, 0);
    PROXY_FENCE_SMEM();
    if (prod) {
      if (kind == 0) product_mma<true>(G->w, pd0, pc0, ring); else product_mma<false>(G->w + kind * 131072, pd0, pc0, ring);
      product_done(&G->ctr[kind ? C_M : C_W]);
    }
    asm volatile("setmaxnreg.dec.sync.aligned.u32 56;\n");
    unsigned ep;
    asm volatile("ld.shared.u32 %0, [%1];" : "=r"(ep) : "r"(sb + SM_BAR + 496) : "memory");
    ep += 1;
    const int w = (threadIdx.x >> 5) & 3;
    if (w == 0) {
      if (lane == 0) {
        uint32_t st = 0, ph = 1;
        auto push = [&](const uint8_t* p, const uint8_t* rem, uint32_t bytes = STB, uint32_t rbytes = 8192) {
          mbar_wait(empty0 + 8 * st, ph);
          mbar_expect_tx(full0 + 8 * st, rem ? bytes + rbytes : bytes);
          bulk_g2s(ring + st * STB, p, bytes, full0 + 8 * st);
          if (rem) bulk_g2s(sb + SM_REM, rem, rbytes, full0 + 8 * st);
          if (++st == NST) { st = 0; ph ^= 1; }
        };
        auto qfill = [&](int e, int h, const uint8_t* p, const unsigned* flag, unsigned target, const float2* meta) {
          if (flag) gwait(flag, target);
          mbar_wait(evt0 + 16 * e + 8 * h, 0);
          PROXY_FENCE_SMEM();
          mbar_expect_tx(qbar0 + 8 * h, meta ? 32768 + 512 : 32768);
          bulk_g2s(sb + SM_Q + h * 32768, p + h * 32768, 32768, qbar0 + 8 * h);
          if (meta) bulk_g2s(sb + SM_META + h * 512, meta, 512, qbar0 + 8 * h);
        };
        auto lload = [&](int u, int blk, uint32_t dst) {
          const uint32_t lfull = xbar0 + 8 * u;
          const uint32_t nd = blk < 156 ? 128 : blk == 156 ? 32 : 0;
          mbar_expect_tx(lfull, 32768 + nd);
          bulk_g2s(dst, at(G->acc, blk * 32768), 32768, lfull);
          if (nd) bulk_g2s(sb + SM_DINV + u * 128, at(deg_inv, blk * 128), nd, lfull);
        };
        gwait(&G->ctr[C_W], ep * CNT_W);
        PROXY_FENCE_SMEM();
        mbar_expect_tx(wfirst, 16384);
        bulk_g2s(ring, G->w, 16384, wfirst);
        mbar_expect_tx(full0, STB - 16384);
        bulk_g2s(ring + 16384, G->w + 16384, STB - 16384, full0);
        st = 1;
#pragma unroll 1
        for (int i = 1; i < 3; i++) push(G->w + i * STB, i == 2 ? G->w + 3 * STB : nullptr);
        mbar_arrive(wsent);
        gwait(&G->ctr[C_E], ep * CNT_E);
#pragma unroll 1
        for (int j = 0; j < n0 + n1; j++) {
          if (j == (owner ? 2 : 1)) gwait(&G->ctr[C_F], ep * CNT_F);
          if (j == 3) gwait(&G->ctr[C_H], ep * CNT_H);
          int kt = j >= n0 ? k1 + j - n0 : owner ? j : NKV - 1 - j;
          if (kt < 3) kt = kt == 2 ? 21 : 123 - kt; else if (kt >= 21 && kt < 24) kt -= 21; else if (kt == 122 || kt == 123) kt -= 100;
          push(at(G->ht, kt * STB), nullptr);
          if (j == JBG) { mbar_arrive(qbar0); mbar_arrive(qbar0 + 8); }
          if (j == JSCAT - (role == 4 ? 2 : 0)) mbar_arrive(go);
          if (j == n0 || j == n0 + 1) qfill(1, j - n0, at(G->qt, q1 * 65536), j == n0 ? &G->ctr[C_M] : nullptr, ep * CNT_M, nullptr);
        }
        const uint8_t* wf = G->w + (owner ? 262144 : 131072);
        const int el = n1 ? 6 : 1;
        auto pfill = [&](int h, bool poll) {
          qfill(el, h, at(G->part, i1 * 65536), poll ? (unsigned*)at(G->pflag, i1 * 8 + h * 4) : nullptr, ep, (float2*)at(G->meta, i1 * 1024 + h * 512));
        };
        asm volatile("prefetch.tensormap [%0];" ::"l"(&omap) : "memory");
        mbar_wait(sdone, 0);
        PROXY_FENCE_SMEM();
        push(wf, wf + (owner ? 2 : 3) * STB, STB, owner ? STB : 8192);
        if (i1 >= 0) pfill(0, true);
        if (!owner) {
          gwait(&G->ctr[C_G], ep * CNT_G);
          if (n1) lload(role == 4 ? 0 : 2, role == 4 ? lu : lu2, sb + SM_AUX);
          if (i1 < 0) { mbar_wait(evt0 + 16 * el, 0); lload(0, lu, sb + SM_Q); }
        }
        push(wf + STB, nullptr);
        bool late = false;
        if (owner) {
          unsigned v, fr;
          do {
            asm volatile("ld.acquire.gpu.global.u32 %0, [%1];" : "=r"(v) : "l"(at(G->pflag, i1 * 8 + 4)) : "memory");
            asm volatile("{\n.reg .pred p;\nmbarrier.test_wait.parity.shared::cta.b64 p, [%1], %2;\nselp.u32 %0, 1, 0, p;\n}\n" : "=r"(fr) : "r"(empty0 + 8 * st), "r"(ph) : "memory");
          } while (v != ep && !fr);
          late = v != ep;
        }
        if (late) push(wf + 3 * STB, nullptr, 8192);
        if (i1 >= 0) pfill(1, late || !owner);
        else { mbar_wait(evt0 + 16 * el + 8, 0); lload(1, lu + 1, sb + SM_Q + 32768); }
        if (!late) push(wf + (owner ? 3 : 2) * STB, nullptr, owner ? 8192 : STB);
        if (role == 4) {
          mbar_wait(evt0 + 80, 0); PROXY_FENCE_SMEM(); mbar_wait(wsent, 1); lload(1, lu + 1, sb + SM_AUX);
          mbar_wait(evt0 + 88, 0); PROXY_FENCE_SMEM(); mbar_wait(wfirst, 1); lload(2, lu2, sb + SM_AUX);
        }
        if (cta == 0) G->epoch = ep;
      }
    } else {
      if (w == 3 && lane == 0) {
        const int pub = role == 0 ? 3 : owner ? 1 : 2;
        if (!early) mbar_wait(wsent, 0);
#pragma unroll 1
        for (int h = 0; h < 2; h++) {
          if (pub >> h & 1) { mbar_wait(evt0 + 64 + 8 * h, 0); bulk_s2g(G->ht + (size_t)q0 * 65536 + h * 32768, sb + SM_Q + h * 32768, cta >= 130 ? 8192 : pub == 3 && h ? 16384 : 32768); }
          BULK_COMMIT();
        }
        asm volatile("cp.async.bulk.wait_group 1;\n" ::: "memory");
        mbar_arrive(hread0);
        if (pub == 3) {
          mbar_wait(empty0, 0);
          __nanosleep(50);
          bulk_s2g(G->ht + (size_t)q0 * 65536 + 49152, sb + SM_Q + 49152, 16384);
          BULK_COMMIT();
        }
        BULK_WAIT();
        mbar_arrive(hread0 + 8);
        GPU_FENCE();
        if (early) garrive_relaxed(&G->ctr[C_E]);
        if (cta > 20 && cta < 25) garrive_relaxed(&G->ctr[C_F]);
        garrive_relaxed(&G->ctr[C_H]);
      }
      __syncwarp();
      mbar_wait(qbar0 + 8, 0);
      if (w < 3) {
        const uint32_t eb = box + 16384;
        if (threadIdx.x == 288) {
          mbar_expect_tx(ebar, ne * 8);
          bulk_g2s(eb, src + e0, ne * 4, ebar);
          bulk_g2s(eb + 8192, dst + e0, ne * 4, ebar);
        }
        __syncwarp();
        mbar_wait(ebar, 0);
#pragma unroll 1
        for (int i = threadIdx.x - 288; i < ne / 4; i += 64) {
          const uint4 vs = lds128(eb + i * 16), vd = lds128(eb + 8192 + i * 16);
          uint32_t tl[4], sl[4];
#pragma unroll
          for (int u = 0; u < 4; u++) {
            tl[u] = comp(vs, u) * 52429u >> 22;
            asm volatile("atom.shared.add.u32 %0, [%1], 1;" : "=r"(sl[u]) : "r"(cnt + tl[u] * 4) : "memory");
          }
#pragma unroll
          for (int u = 0; u < 4; u++)
            if (sl[u] < 32) asm volatile("st.shared.u32 [%0], %1;" ::"r"(box + tl[u] * 128 + sl[u] * 4), "r"(0x80000000u | (comp(vs, u) - tl[u] * BN) << 14 | comp(vd, u)) : "memory");
          if ((sl[0] | sl[1] | sl[2] | sl[3]) >= 32) {
#pragma unroll 1
            for (int u = 0; u < 4; u++) {
              const uint32_t a = u & 1 ? (u & 2 ? sl[3] : sl[1]) : (u & 2 ? sl[2] : sl[0]);
              if (a >= 32) {
                uint32_t k;
                asm volatile("atom.shared.add.u32 %0, [%1], 1;" : "=r"(k) : "r"(cnt + NKV * 4) : "memory");
                G->ovf[cta * 1280 + k] = comp(vs, u) << 14 | comp(vd, u);
              }
            }
          }
        }
        PROXY_FENCE_SMEM();
        bar_arrive(8, 96);
      }
      if (w == 3) {
#pragma unroll 4
        for (int i = 0; i < 16; i++) sts128(sb + SM_REM + i * 512 + lane * 16, 0, 0, 0, 0);
        PROXY_FENCE_SMEM();
        bar_sync(8, 96);
        if (lane == 0) {
#pragma unroll 1
          for (int i = 0; i < 5; i++) {
            const size_t off = (size_t)cta * 40960 + i * 8192;
            if (cta < NKV) { mbar_expect_tx(bbar, 8192); bulk_g2s(box + 16384, (const uint8_t*)x + off, 8192, bbar); }
            bulk_s2g(G->acc + off, sb + SM_REM, 8192);
            if (cta < NKV) { mbar_wait(bbar, i & 1); bulk_s2g((uint8_t*)out + off, box + 16384, 8192); }
            BULK_COMMIT();
            BULK_WAIT();
          }
          if (cta < 130 && role < 2) {
            mbar_wait(evt0, 0);
            mbar_wait(evt0 + 8, 0);
#pragma unroll 1
            for (int i = 0; i < 8; i++) {
              bulk_s2g(G->qt + (size_t)q0 * 65536 + i * 8192, sb + SM_Q + i * 8192, 8192);
              BULK_COMMIT();
              BULK_WAIT();
            }
          }
        }
        __syncwarp();
        bar_arrive(6, 96);
        if (lane == 0 && !owner) {
#pragma unroll 1
          for (int u = n1 ? 0 : 2; u < 4; u++) {
            mbar_wait(evt0 + 32 + 8 * u, 0);
            if (staged && u == 0) {
              mbar_wait(evt0 + 40, 0);
#pragma unroll 1
              for (int i = 0; i < 10; i++) {
                bulk_s2g(G->part + (size_t)o0 * 65536 + (i < 5 ? i * 4096 : 12288 + i * 4096), sb + SM_REM + i * 4096, 4096);
                BULK_COMMIT();
                BULK_WAIT();
              }
              mbar_arrive(sfree);
            }
            gset(&G->pflag[(u < 2 || !n1 ? o0 : q1) * 2 + (u & 1)], ep);
            if (u >= 2) mbar_arrive(u == 2 ? wsent : wfirst);
          }
        }
      } else {
        bar_sync(6, 96);
        int novf;
        asm volatile("ld.shared.u32 %0, [%1];" : "=r"(novf) : "r"(cnt + NKV * 4) : "memory");
        if (threadIdx.x == 288) {
          bulk_s2g(G->box + cta * NKV * 32, box, NKV * 128);
          BULK_COMMIT();
          BULK_WAIT();
          garrive(&G->ctr[C_M]);
          gwait(&G->ctr[C_H], ep * CNT_H);
          if (staged) mbar_wait(sfree, 0);
          if (cta < NKV) { mbar_expect_tx(bbar, STB); bulk_g2s(sb + SM_REM, G->ht + (size_t)cta * STB, STB, bbar); }
        }
        __syncwarp();
        if (cta < NKV) {
          mbar_wait(bbar, 1);
#pragma unroll 1
          for (int gi = 0; gi < 10; gi++) {
            uint4 v[4];
#pragma unroll
            for (int u = 0; u < 4; u++) { const int rr = (w - 1) * 4 + u; v[u] = lds128(sb + SM_REM + gi * 4096 + (lane >> 3) * 1024 + rr * 128 + (((lane ^ rr) & 7) << 4)); }
            bar_sync(5, 64);
#pragma unroll
            for (int u = 0; u < 4; u++) sts128(sb + SM_REM + gi * 4096 + ((w - 1) * 4 + u) * 512 + lane * 16, v[u].x, v[u].y, v[u].z, v[u].w);
          }
          PROXY_FENCE_SMEM();
          bar_sync(5, 64);
        }
        mbar_wait(go, 0);
        if (lane == 0) gwait(&G->ctr[C_M], ep * CNT_M);
        __syncwarp();
        if (cta < NKV) {
          const unsigned* bp = (unsigned*)at(G->box, ((w - 1) * NKV + cta) * 128 + lane * 4);
          unsigned e = __ldcg(bp);
#pragma unroll 1
          for (int i = 0; i < NCTA / 2; i++) {
            bp += 2 * NKV * 32;
            unsigned en = 0;
            if (i + 1 < NCTA / 2) en = __ldcg(bp);
            if (e) bulk_red(G->acc + (size_t)(e & 0x3fff) * 512, sb + SM_REM + ((e >> 14) & 127) * 512, 512);
            BULK_COMMIT();
            BULK_WAIT_READ();
            e = en;
          }
        }
#pragma unroll 1
        for (int i = w - 1; i < novf; i += 2) {
          const int e = __ldcg(&G->ovf[cta * 1280 + i]), r = e >> 14;
          const uint4 v = ldg_cg(G->ht + (size_t)(r >> 3) * 4096 + (lane >> 3) * 1024 + (r & 7) * 128 + (((lane ^ r) & 7) << 4));
          asm volatile("red.global.add.noftz.v4.bf16x2 [%0], {%1,%2,%3,%4};" ::"l"(G->acc + (size_t)(e & 0x3fff) * 512 + lane * 16), "r"(v.x), "r"(v.y), "r"(v.z), "r"(v.w) : "memory");
        }
        BULK_WAIT();
        __syncwarp();
        if (lane == 0) { mbar_arrive(sdone); garrive(&G->ctr[C_G]); }
      }
    }
  } else {
    const int g = lane >> 2, t = lane & 3, wp = __shfl_sync(~0u, (threadIdx.x >> 5) & 3, 0), tid = threadIdx.x & 127;
    const uint32_t qh = sb + SM_Q + wg * 32768;
    const uint32_t qw = qh + wp * 8192;
    const uint32_t qbar = qbar0 + 8 * wg;
    auto event = [&](int e) { mbar_arrive(evt0 + 16 * e + 8 * wg); };
    if (wg == 1) bar_arrive(1, 256);
    {
      const int xr0 = min(q0 * 128 + wg * 64 + wp * 16, N_ - 16), xord = (owner || !early ? wg : wg ^ 1) * 4 + wp;
      if (cta >= 64 && xord >= 4) mbar_wait(xbar0 + 8 * (xord - 4), 0);
      if (lane == 0 && xord >= xfirst) {
        mbar_expect_tx(xbar0 + 8 * xord, 8192);
        bulk_g2s(qw, at(x, xr0 * 512), 8192, xbar0 + 8 * xord);
      }
      mbar_wait(xbar0 + 8 * xord, 0);
      uint4 xa[8], xb[8];
      const uint32_t sw = (g & 1) << 6;
#pragma unroll
      for (int J = 0; J < 8; J++) xa[J] = lds128(qw + g * 512 + t * 16 + ((J * 64) ^ sw));
#pragma unroll
      for (int J = 0; J < 8; J++) xb[J] = lds128(qw + 4096 + g * 512 + t * 16 + ((J * 64) ^ sw));
      __syncwarp();
      const uint32_t wa = qw + g * 128 + (((t ^ g) << 4) ^ sw);
#pragma unroll
      for (int rr = 0; rr < 2; rr++) {
        float sm[2][4] = {}, f[64], q[4] = {};
#pragma unroll
        for (int J = 0; J < 8; J++) {
          const uint4 v = rr ? xb[J] : xa[J];
          mma16816(sm[J & 1], v.x, v.y, v.z, v.w, 0x3f803f80u, 0x3f803f80u);
#pragma unroll
          for (int i = 0; i < 4; i++) {
            f[J * 8 + 2 * i] = blo(comp(v, i)); f[J * 8 + 2 * i + 1] = bhi(comp(v, i));
            q[i] = fmaf(f[J * 8 + 2 * i], f[J * 8 + 2 * i], q[i]); q[i ^ 2] = fmaf(f[J * 8 + 2 * i + 1], f[J * 8 + 2 * i + 1], q[i ^ 2]);
          }
        }
        const float mean = ((sm[0][0] + sm[0][2]) + (sm[1][0] + sm[1][2])) * (1.f / 256.f);
        float rstd = rsq(fmaxf(fmaf(-mean, mean, quad_sum((q[0] + q[1]) + (q[2] + q[3])) * (1.f / 256.f)), 0.f) + 1e-5f);
        if (q0 * 8 + wg * 4 + wp >= N_ / 16) rstd = 0.f;
#pragma unroll
        for (int J = 0; J < 8; J++) {
          const bool lastc = J >= 6 && (lane & 7) == (J == 7 ? 3 : 7);
          const float c = (lastc ? f[J * 8 + 7] : mean) * -rstd;
          uint32_t r3 = pack2(fmaf(f[J * 8 + 6], rstd, c), fmaf(f[J * 8 + 7], rstd, c));
          if (lastc) r3 = (r3 & 0xffffu) | 0x3f800000u;
          sts128((wa ^ ((J & 1) << 6)) + rr * 4096 + (J >> 1) * 1024, pack2(fmaf(f[J * 8], rstd, c), fmaf(f[J * 8 + 1], rstd, c)),
                 pack2(fmaf(f[J * 8 + 2], rstd, c), fmaf(f[J * 8 + 3], rstd, c)), pack2(fmaf(f[J * 8 + 4], rstd, c), fmaf(f[J * 8 + 5], rstd, c)), r3);
        }
      }
      PROXY_FENCE_SMEM();
    }
    event(4);
    bar_sync(3 + wg, 128);
    asm volatile("setmaxnreg.inc.sync.aligned.u32 224;\n");

    float o[128];
    uint32_t ga[64], qr[4];
    uint32_t st = 0, ph = 0, pst = 0;
    const uint32_t qd = mkdesc(qh, 16), kd0 = mkdesc(ring, 16), vd0 = mkdesc(ring, 1024), rd = mkdesc(sb + SM_REM, 1024);
    auto wait_full = [&]() { mbar_wait(full0 + 8 * st, ph); };
    auto advance = [&]() { pst = st; if (++st == NST) { st = 0; ph ^= 1; } };
    auto release = [&]() { if (lane == 0) mbar_arrive(empty0 + 8 * pst); };

    {
      mbar_wait(wfirst, 0);
      bar_sync(1 + wg, 256);
      WG_FENCE();
      wgmma_ss256(o, qd, vd0, 0);
      wgmma_ss256(o, qd + 2, vd0 + 512, 1);
#pragma unroll
      for (int c = 0; c < 3; c++) {
        wait_full();
        WG_FENCE();
#pragma unroll
        for (int k = c ? 0 : 2; k < 5; k++) {
          const int ks = c * 5 + k;
          wgmma_ss256(o, qd + (ks >> 2) * 64 + (ks & 3) * 2, vd0 + c * (STB >> 4) + k * 512, 1);
          if (c > 0 && k == 0) { WG_COMMIT(); WG_WAIT(1); release(); }
        }
        if (c == 2) wgmma_ss256(o, qd + 3 * 64 + 6, rd, 1);
        WG_COMMIT();
        if (c == 2) bar_arrive(2 - wg, 256);
        advance();
      }
      WG_WAIT(0);
      pin(o);
      release();
#pragma unroll
      for (int i = 0; i < 64; i++) ga[i] = pack2(o[2 * i], o[2 * i + 1]);
    }
    auto store_q = [&]() {
      mbar_wait(hread0 + 8 * wg, 0);
      bar_sync(3 + wg, 128);
      const uint32_t sa = qw + ((lane >> 3) & 1) * 4096 + (lane & 7) * 128 + (((lane >> 4) ^ (lane & 7)) << 4);
#pragma unroll
      for (int i = 0; i < 16; i++) stsm4((sa ^ ((i & 3) << 5)) + (i >> 2) * 1024, ga[4 * i], ga[4 * i + 1], ga[4 * i + 2], ga[4 * i + 3]);
      PROXY_FENCE_SMEM();
      event(0);
    };
    if (wg == 0) store_q();

    float s[BN / 2];
    uint32_t p[BN / 4];
    float m0, m1, l0, l1, cb0 = 0.f, cb1 = 0.f;
    auto qk = [&]() {
#pragma unroll
      for (int i = 0; i < 16; i++) {
        const int ks = (i + 15) & 15;
        const uint32_t off = (ks >> 2) * 64 + (ks & 3) * 2;
        const uint64_t q64 = (uint64_t)DESC_HI << 32 | qd, k64 = ((uint64_t)DESC_HI << 32 | kd0) + st * (STB >> 4);
        if (ks < 15) wgmma_qk64(s, q64 + off, k64 + off, 1);
        else wgmma_qkr64(s, qr[0], qr[1], qr[2], qr[3], k64 + off, 0);
      }
      WG_COMMIT();
    };
    auto pv = [&](int keep) {
#pragma unroll
      for (int ks = 0; ks < BN / 16; ks++) wgmma_pv64(o, p[ks * 4], p[ks * 4 + 1], p[ks * 4 + 2], p[ks * 4 + 3], ((uint64_t)DESC_HI << 32 | vd0) + pst * (STB >> 4) + ks * 512, ks ? 1 : keep);
      WG_COMMIT();
    };
    auto softmax_slow = [&](bool dump, bool first) {
      const float om0 = m0, om1 = m1;
      const uint32_t ok = first ? 0 : pack2(m0, m1);
      const float mb0 = blo(ok), mb1 = bhi(ok);
      if (dump) {
        m0 = m1 = -INFINITY;
        if (staged) {
#pragma unroll
          for (int k = 0; k < 10; k++)
            sts128(sb + SM_REM + wg * 20480 + k * 2048 + tid * 16, pack2(o[8 * k], o[8 * k + 1]), pack2(o[8 * k + 2], o[8 * k + 3]), pack2(o[8 * k + 4], o[8 * k + 5]), pack2(o[8 * k + 6], o[8 * k + 7]));
        }
      }
      float x0 = fmaxf(s[0], s[1]), x1 = fmaxf(s[2], s[3]);
#pragma unroll
      for (int i = 1; i < BN / 8; i++) { x0 = fmaxf(x0, fmaxf(s[4 * i], s[4 * i + 1])); x1 = fmaxf(x1, fmaxf(s[4 * i + 2], s[4 * i + 3])); }
      x0 = quad_max(x0) + mb0; x1 = quad_max(x1) + mb1;
      float r0 = x0 < m0 ? m0 : ceilf(x0 + OFFS), r1 = x1 < m1 ? m1 : ceilf(x1 + OFFS);
      uint32_t pk = pack2(r0, r1);
      const float b0 = blo(pk), b1 = bhi(pk);
      const bool ok0 = fabsf(b0 - r0) <= 8.f, ok1 = fabsf(b1 - r1) <= 8.f;
      if (ok0) r0 = b0;
      if (ok1) r1 = b1;
      const float a0 = ex2(m0 - r0), a1 = ex2(m1 - r1), d0 = r0 - mb0, d1 = r1 - mb1;
      m0 = r0; m1 = r1;
      if (t == 3) {
        pk ^= 0x80008000u;
        qr[2] = __byte_perm(qr[2], pk, 0x5410);
        qr[3] = __byte_perm(qr[3], pk, 0x7610);
      }
      if (dump) {
        if (t == 3) {
          float2* mp = (float2*)at(G->meta, (o0 * 128 + wg * 64 + wp * 16 + g) * 8);
          mp[0] = make_float2(om0, o[125]);
          mp[8] = make_float2(om1, o[127]);
        }
        uint8_t* pp = at(G->part, o0 * 65536 + wg * 32768 + tid * 16);
#pragma unroll
        for (int k = 15; k >= 0; k--) {
          if (k == 9 && staged) break;
          stg128(pp + k * 2048, pack2(o[8 * k], o[8 * k + 1]), pack2(o[8 * k + 2], o[8 * k + 3]), pack2(o[8 * k + 4], o[8 * k + 5]), pack2(o[8 * k + 6], o[8 * k + 7]));
        }
      }
      if (!first && __any_sync(~0u, a0 != 1.f || a1 != 1.f)) {
        cb0 *= a0; cb1 *= a1;
#pragma unroll
        for (int i = 0; i < 32; i++) { o[4 * i] *= a0; o[4 * i + 1] *= a0; o[4 * i + 2] *= a1; o[4 * i + 3] *= a1; }
      }
#pragma unroll
      for (int i = 0; i < BN / 8; i++) {
        p[2 * i] = pack2(ex2(s[4 * i] - d0), ex2(s[4 * i + 1] - d0));
        p[2 * i + 1] = pack2(ex2(s[4 * i + 2] - d1), ex2(s[4 * i + 3] - d1));
      }
      return (bool)__any_sync(~0u, !(ok0 && ok1));
    };
    {
      int left = n0 + n1 - 1;
      if (cta >= 130 && wg) {
#pragma unroll 1
        for (; left > 1; left--) {
          wait_full();
          bar_sync(2, 256);
          bar_arrive(1, 256);
          advance();
          release();
        }
      }
      wait_full();
      bar_sync(1 + wg, 256);
      WG_FENCE();
#pragma unroll
      for (int ks = 0; ks < 16; ks++)
        wgmma_qkr64(s, ga[4 * ks], ga[4 * ks + 1], ga[4 * ks + 2], ga[4 * ks + 3], ((uint64_t)DESC_HI << 32 | kd0) + st * (STB >> 4) + (ks >> 2) * 64 + (ks & 3) * 2, ks);
      WG_COMMIT();
      bar_arrive(2 - wg, 256);
      m0 = m1 = -INFINITY;
      WG_WAIT(0);
      pin(s);
#pragma unroll
      for (int i = 0; i < 64; i++) asm volatile("" : "+r"(ga[i])::"memory");
      if (wg) store_q();
#pragma unroll
      for (int i = 0; i < 4; i++) qr[i] = ga[60 + i];
      bool slow = softmax_slow(false, true);
#pragma unroll
      for (int i = 0; i < 128; i++) asm volatile("" : "=f"(o[i]));
      int keep = 0, stage = 0, trig = left + 1 - B0;
      advance();
#pragma unroll 1
      do {
        const bool sw = left == n1;
        wait_full();
        bar_sync(1 + wg, 256);
        WG_FENCE();
        pv(keep);
        keep = !sw;
        if (sw) {
          mbar_wait(qbar, 1);
          slow = true;
          ldsm4(qr, qw + ((lane >> 3) & 1) * 4096 + 3 * 1024 + (lane & 7) * 128 + (((6 + (lane >> 4)) ^ (lane & 7)) << 4));
        }
        WG_FENCE();
        qk();
        bar_arrive(2 - wg, 256);
        WG_WAIT(1);
        release();
        WG_WAIT(0);
        pin(s); pin(o);
        left--;
        if (left == n1 || left == 0) event(left == n1 ? 1 : 6);
        if (!slow) {
          uint32_t acc = 0;
#pragma unroll
          for (int i = 0; i < BN / 4; i++) { p[i] = pack2(ex2(s[2 * i]), ex2(s[2 * i + 1])); acc |= p[i]; }
          slow = __any_sync(~0u, (acc & 0x40004000u) != 0);
        }
        if (slow) {
          slow = softmax_slow(sw, sw);
        }
        auto offset = [&](int r, float& cb) {
          float c = __uint_as_float((__float_as_uint(__shfl_sync(~0u, o[125 + 2 * r], lane | 3) * BETA) & 0x7f800000u) | 0x2aaa00u);
          if (stage >= 2) c = stage == 2 ? -cb : 0.f;
          const float d = c - cb;
          cb = c;
#pragma unroll
          for (int i = 0; i < 64; i++) o[(i >> 1) * 4 + 2 * r + (i & 1)] += i == 63 && t == 3 ? 0.f : i < 32 ? d : -d;
        };
        if (left == trig) offset(0, cb0);
        pin(o);
        if (left == trig - 1) {
          offset(1, cb1);
          if (left == n1 - 1 - B0) { PROXY_FENCE_SMEM(); event(2); }
          const int end = left >= n1 ? n1 : 0;
          if (stage == 0 && left - end <= 24) stage = 1;
          trig = stage == 0 ? trig - (B1 - B0) : stage == 1 ? (trig + end + 2) >> 1 : stage == 2 ? end + 2 : end - B0;
          stage = (stage + 1) & 3;
        }
        advance();
      } while (left);
      bar_sync(1 + wg, 256);
      WG_FENCE();
      pv(1);
      bar_arrive(2 - wg, 256);
      WG_WAIT(0);
      pin(o);
      release();
      if (i1 >= 0) {
        mbar_wait(qbar, n1 ? 0 : 1);
        const uint32_t ma = sb + SM_META + wg * 512 + (wp * 16 + g) * 8;
        float2 h0, h1;
        asm volatile("ld.shared.v2.f32 {%0,%1}, [%2];" : "=f"(h0.x), "=f"(h0.y) : "r"(ma) : "memory");
        asm volatile("ld.shared.v2.f32 {%0,%1}, [%2];" : "=f"(h1.x), "=f"(h1.y) : "r"(ma + 64) : "memory");
#pragma unroll
        for (int k = 0; k < 16; k++) { const uint4 v = lds128(qh + k * 2048 + tid * 16); ga[4 * k] = v.x; ga[4 * k + 1] = v.y; ga[4 * k + 2] = v.z; ga[4 * k + 3] = v.w; }
        if (__any_sync(~0u, h0.x - m0 > 20.f || h1.x - m1 > 20.f)) {
          const float t0 = fmaxf(m0, h0.x), t1 = fmaxf(m1, h1.x), a0 = ex2(m0 - t0), a1 = ex2(m1 - t1);
          m0 = t0; m1 = t1;
#pragma unroll
          for (int i = 0; i < 32; i++) { o[4 * i] *= a0; o[4 * i + 1] *= a0; o[4 * i + 2] *= a1; o[4 * i + 3] *= a1; }
        }
        const float b0 = ex2(h0.x - m0), b1 = ex2(h1.x - m1);
        l0 = fmaf(b0, h0.y, o[125]); l1 = fmaf(b1, h1.y, o[127]);
        const uint32_t bb0 = pack2(b0, b0), bb1 = pack2(b1, b1);
#pragma unroll
        for (int i = 0; i < 64; i++) ga[i] = hfma2(ga[i], (i & 1) ? bb1 : bb0, pack2(o[2 * i], o[2 * i + 1]));
      } else {
        l0 = o[125]; l1 = o[127];
#pragma unroll
        for (int i = 0; i < 64; i++) ga[i] = pack2(o[2 * i], o[2 * i + 1]);
      }
      if (!owner) {
        if (wg) mbar_wait(wsent, 1);
        const int slot = n1 ? q1 : o0;
        uint8_t* pp = at(G->part, slot * 65536 + wg * 32768 + tid * 16);
#pragma unroll
        for (int k = 0; k < 16; k++) stg128(pp + k * 2048, ga[4 * k], ga[4 * k + 1], ga[4 * k + 2], ga[4 * k + 3]);
        if (t == 3) {
          float2* mp = (float2*)at(G->meta, (slot * 128 + wg * 64 + wp * 16 + g) * 8);
          mp[0] = make_float2(m0, l0);
          mp[8] = make_float2(m1, l1);
        }
        event(3);
      }
    }

    float f0 = rcp(__shfl_sync(~0u, l0, lane | 3)), f1 = rcp(__shfl_sync(~0u, l1, lane | 3));
#pragma unroll 1
    for (int rnd = 0;; rnd++) {
      int r0 = q0 * 128 + wg * 64;
      if (!owner) {
        r0 = (rnd ? lu2 : lu + wg) * 64;
        mbar_wait(xbar0 + 8 * (rnd * 2 + wg), 1);
        const uint32_t la = (rnd || role == 4 ? sb + SM_AUX + wp * 8192 : qw) + g * 512 + t * 16;
#pragma unroll
        for (int J = 0; J < 8; J++) {
          const uint4 va = lds128(la + J * 64), vb = lds128(la + 4096 + J * 64);
          ga[8 * J] = va.x; ga[8 * J + 1] = vb.x; ga[8 * J + 2] = va.y; ga[8 * J + 3] = vb.y;
          ga[8 * J + 4] = va.z; ga[8 * J + 5] = vb.z; ga[8 * J + 6] = va.w; ga[8 * J + 7] = vb.w;
        }
        uint32_t d0, d1;
        asm volatile("ld.shared.u16 %0, [%1];" : "=r"(d0) : "r"(sb + SM_DINV + (rnd * 128 + wg * 64 + wp * 16 + g) * 2) : "memory");
        asm volatile("ld.shared.u16 %0, [%1];" : "=r"(d1) : "r"(sb + SM_DINV + (rnd * 128 + wg * 64 + wp * 16 + g + 8) * 2) : "memory");
        f0 = blo(d0); f1 = blo(d1);
        if (rnd == 0) event(5);
      }
      r0 += wp * 16;
#pragma unroll
      for (int i = 0; i < 64; i++) asm volatile("" : "+r"(ga[i])::"memory");
      BULK_WAIT_READ();
      float oa[64], ob[64];
      pin(oa); pin(ob);
      const uint32_t sa = qw + (lane & 15) * 128 + (((lane >> 4) ^ (lane & 7)) << 4);
      auto stage = [&](const float (&v)[64], int h, int i) {
        stsm4((sa ^ ((i & 3) << 5)) + (h * 2 + (i >> 2)) * 2048, pack2(v[8 * i] * f0, v[8 * i + 1] * f0), pack2(v[8 * i + 2] * f1, v[8 * i + 3] * f1),
              pack2(v[8 * i + 4] * f0, v[8 * i + 5] * f0), pack2(v[8 * i + 6] * f1, v[8 * i + 7] * f1));
      };
      auto send = [&](int h) {
        PROXY_FENCE_SMEM();
        __syncwarp();
        if (lane == 0) {
#pragma unroll
          for (int b = 2 * h; b < 2 * h + 2; b++)
            asm volatile("cp.reduce.async.bulk.tensor.2d.global.shared::cta.add.tile.bulk_group [%0, {%1, %2}], [%3];" ::"l"(&omap), "r"(b * 64), "r"(r0), "r"(qw + b * 2048) : "memory");
          BULK_COMMIT();
        }
      };
      bar_sync(1 + wg, 256);
      uint32_t wd[3], wl = rd;
#pragma unroll
      for (int c = 0; c < 3; c++) {
        if (rnd == 0 && (c < 2 || !owner)) wait_full();
        WG_FENCE();
        wd[c] = vd0 + st * (STB >> 4);
        if (c == 2 && owner) { wl = wd[2]; wd[2] = rd; }
#pragma unroll
        for (int k = 0; k < 5; k++) { const int ks = c * 5 + k; wgmma_rs128(oa, ga[ks * 4], ga[ks * 4 + 1], ga[ks * 4 + 2], ga[ks * 4 + 3], wd[c] + k * 512, ks != 0); }
        if (c == 2) { if (owner) wait_full(); WG_FENCE(); }
        advance();
      }
      wgmma_rs128(oa, ga[60], ga[61], ga[62], ga[63], wl, 1);
      WG_COMMIT();
#pragma unroll
      for (int ks = 0; ks < 16; ks++) {
        wgmma_rs128(ob, ga[ks * 4], ga[ks * 4 + 1], ga[ks * 4 + 2], ga[ks * 4 + 3], (ks < 15 ? wd[ks / 5] + (ks % 5) * 512 : wl) + 128, ks != 0);
        if (ks == 1) { WG_COMMIT(); WG_WAIT(1); pin(oa); }
        if (ks >= 1 && ks < 9) stage(oa, 0, ks - 1);
      }
      WG_COMMIT();
      if (wg == 0 ? rnd == 0 : n1 != 0) bar_arrive(2 - wg, 256);
      send(0);
      WG_WAIT(0);
      pin(ob);
#pragma unroll
      for (int i = 0; i < 8; i++) stage(ob, 1, i);
      send(1);
      if (rnd || wg || !n1) break;
    }
    BULK_WAIT_READ();
  }
}

}

extern "C" void kernel_launch(void* const* d_in, const int* in_sizes, int n_in, void* d_out, int out_size) {
  (void)in_sizes; (void)n_in; (void)out_size;
  void* scratch = nullptr;
  cudaGetSymbolAddress(&scratch, g_scratch);
  typedef CUresult (*Encode)(CUtensorMap*, CUtensorMapDataType, cuuint32_t, void*, const cuuint64_t*, const cuuint64_t*, const cuuint32_t*,
                             const cuuint32_t*, CUtensorMapInterleave, CUtensorMapSwizzle, CUtensorMapL2promotion, CUtensorMapFloatOOBfill);
  void* fn = nullptr;
  cudaDriverEntryPointQueryResult qr;
  cudaGetDriverEntryPoint("cuTensorMapEncodeTiled", &fn, cudaEnableDefault, &qr);
  CUtensorMap omap;
  const cuuint64_t dims[2] = {256, N_}, strides[1] = {512};
  const cuuint32_t box[2] = {64, 16}, estr[2] = {1, 1};
  ((Encode)fn)(&omap, CU_TENSOR_MAP_DATA_TYPE_BFLOAT16, 2, d_out, dims, strides, box, estr, CU_TENSOR_MAP_INTERLEAVE_NONE,
               CU_TENSOR_MAP_SWIZZLE_128B, CU_TENSOR_MAP_L2_PROMOTION_NONE, CU_TENSOR_MAP_FLOAT_OOB_FILL_NONE);
  cudaFuncSetAttribute(gps_kernel, cudaFuncAttributeMaxDynamicSharedMemorySize, SM_TOTAL);
  gps_kernel<<<NCTA, 384, SM_TOTAL>>>((const __nv_bfloat16*)d_in[0], (const int*)d_in[1], (const int*)d_in[2],
                                      (const __nv_bfloat16*)d_in[3], (const __nv_bfloat16*)d_in[4], (const __nv_bfloat16*)d_in[5],
                                      (const __nv_bfloat16*)d_in[6], (const __nv_bfloat16*)d_in[7], (const __nv_bfloat16*)d_in[8],
                                      (__nv_bfloat16*)d_out, (Scratch*)scratch, omap);
}
```
